```python
import torch

def _softmax(x, axis=-1):
    return torch.softmax(x, dim=axis)
def _gelu(x):
    return torch.nn.functional.gelu(x, approximate="tanh")
def _silu(x):
    return torch.nn.functional.silu(x)
def _sigmoid(x):
    return torch.sigmoid(x)
def _layernorm(x, axis=-1, eps=1e-5):
    m = x.mean(dim=axis, keepdim=True)
    v = x.var(dim=axis, keepdim=True, unbiased=False)
    return (x - m) / torch.sqrt(v + eps)
def _scatter_add(tgt, idx, src, axis=0):
    return tgt.clone().index_add_(axis, idx, src)
def _segment_sum(src, seg, n):
    out = torch.zeros((n,) + src.shape[1:], dtype=src.dtype)
    return out.index_add_(0, seg, src)
def _pad(x, pw):
    flat = tuple(v for pair in reversed(pw) for v in pair)
    return torch.nn.functional.pad(x, flat)

kernel_name = 'interleave_layers__sliding_local_dilated__glu_gated_bilinear__prompt'

def setup_inputs():

    _w = (lambda a: (lambda t: t.to(torch.bfloat16) if t.is_floating_point() else t)(torch.as_tensor(a)))
    def _A_setup():
        B, S, D = 1, 2048, 576
        return {
            "x": _w((lambda *s: torch.randn(*s, dtype=torch.bfloat16) * 0.05)(B, S, D)),
            "wqkv": _w((lambda *s: torch.randn(*s, dtype=torch.bfloat16) * 0.05)(D, 3 * D)),
            "wo": _w((lambda *s: torch.randn(*s, dtype=torch.bfloat16) * 0.05)(D, D)),
        }
    _A_in = _A_setup()

    def _B_setup():
        B, S, D, F = 1, 2048, 576, 4608
        return {
            "x": _w((lambda *s: torch.randn(*s, dtype=torch.bfloat16) * 0.05)(B, S, D)),
            "w_gate": _w((lambda *s: torch.randn(*s, dtype=torch.bfloat16) * 0.8)(D, F) * (D ** -0.5)),
            "w_up": _w((lambda *s: torch.randn(*s, dtype=torch.bfloat16) * 0.8)(D, F) * (D ** -0.5)),
            "w_down": _w((lambda *s: torch.randn(*s, dtype=torch.bfloat16) * 0.8)(F, D) * (F ** -0.5)),
        }
    _B_in = _B_setup()

    return {
        "A_x": _A_in["x"],
        "A_wqkv": _A_in["wqkv"],
        "A_wo": _A_in["wo"],
        "B_x": _B_in["x"],
        "B_w_gate": _B_in["w_gate"],
        "B_w_up": _B_in["w_up"],
        "B_w_down": _B_in["w_down"],
    }

def reference(A_x, A_wqkv, A_wo, B_x, B_w_gate, B_w_up, B_w_down):
    def _A_ref(x, wqkv, wo):
        B, S, D = x.shape
        H = 32; Dh = D // H
        W, dil = 8, 2
        qkv = (lambda x, *d: x.permute(*d))((x @ wqkv).reshape(B, S, 3, H, Dh), 2, 0, 3, 1, 4)
        q, k, v = qkv[0], qkv[1], qkv[2]
        scale = Dh ** -0.5
        pos = torch.arange(S)
        off = torch.arange(W) * dil
        idx = pos[:, None] - off[None, :]
        mask = idx >= 0
        idx_c = torch.where(mask, idx, 0).reshape(-1)
        kg = k[:, :, idx_c, :].reshape(B, H, S, W, Dh)
        vg = v[:, :, idx_c, :].reshape(B, H, S, W, Dh)
        logits = torch.einsum("bhsd,bhswd->bhsw", q, kg) * scale
        logits = torch.where(mask[None, None, :, :], logits, -1e9)
        attn = _softmax(logits, axis=-1)
        o = torch.einsum("bhsw,bhswd->bhsd", attn, vg)
        return (lambda x, *d: x.permute(*d))(o, 0, 2, 1, 3).reshape(B, S, D) @ wo

    def _B_ref(x, w_gate, w_up, w_down):
        g = torch.einsum("bsd,df->bsf", x, w_gate)
        u = torch.einsum("bsd,df->bsf", x, w_up)
        h = g * u
        return torch.einsum("bsf,fd->bsd", h, w_down)

    x = A_x
    x = x + _A_ref(_layernorm(x, axis=-1), A_wqkv, A_wo)
    x = x + _B_ref(_layernorm(x, axis=-1), B_w_gate, B_w_up, B_w_down)
    x = x + _A_ref(_layernorm(x, axis=-1), A_wqkv, A_wo)
    x = x + _B_ref(_layernorm(x, axis=-1), B_w_gate, B_w_up, B_w_down)
    return x
```

```cpp
#include <cuda_runtime.h>
#include <cuda_bf16.h>
#include <cuda.h>
#include <stdint.h>

namespace {

constexpr int SEQ = 2048, DM = 576, FF = 4608, NQKV = 1728;

__device__ __align__(128) uint4 g_halo[128 * 384];
__device__ __align__(128) uint4 g_stat[SEQ];
__device__ __align__(128) float g_csq[4 * NQKV];
__device__ __align__(128) float g_wsum[DM];
constexpr int FL_J = 64 * 32;
__device__ __align__(128) unsigned int g_flag[FL_J + 32];
__device__ unsigned int g_epoch[128];
__device__ unsigned int g_claim[8];

__device__ __forceinline__ uint32_t smem_u32(const void* p) { return (uint32_t)__cvta_generic_to_shared(p); }
__device__ __forceinline__ void mbar_init(uint32_t bar, uint32_t count) {
  asm volatile("mbarrier.init.shared::cta.b64 [%0], %1;" ::"r"(bar), "r"(count) : "memory");
}
__device__ __forceinline__ void mbar_expect_tx(uint32_t bar, uint32_t bytes) {
  asm volatile("mbarrier.arrive.expect_tx.shared::cta.b64 _, [%0], %1;" ::"r"(bar), "r"(bytes) : "memory");
}
__device__ __forceinline__ void mbar_arrive(uint32_t bar) {
  asm volatile("mbarrier.arrive.shared::cta.b64 _, [%0];" ::"r"(bar) : "memory");
}
#define SPIN_LIMIT "1048576"
#define SPIN_MAX 1048576
__device__ __forceinline__ void mbar_wait(uint32_t bar, uint32_t parity) {
  asm volatile(
      "{\n.reg .pred p, c;\n.reg .u32 n;\nmov.u32 n, 0;\n"
      "WAIT:\nmbarrier.try_wait.parity.shared::cta.b64 p, [%0], %1;\n"
      "add.u32 n, n, 1;\nsetp.lt.and.u32 c, n, " SPIN_LIMIT ", !p;\n@c bra.uni WAIT;\n}"
      :
      : "r"(bar), "r"(parity)
      : "memory");
}
__device__ __forceinline__ bool mbar_test(uint32_t bar, uint32_t parity) {
  uint32_t r;
  asm volatile("{\n.reg .pred p;\nmbarrier.try_wait.parity.shared::cta.b64 p, [%1], %2;\nselp.u32 %0, 1, 0, p;\n}"
               : "=r"(r) : "r"(bar), "r"(parity) : "memory");
  return r != 0;
}
__device__ __forceinline__ void poll_ge(const unsigned int* p, unsigned int target) {
  asm volatile(
      "{\n.reg .pred p, c;\n.reg .u32 n;\n.reg .s32 v;\nmov.u32 n, 0;\n"
      "POLL:\nld.relaxed.gpu.global.u32 v, [%0];\nsub.s32 v, v, %1;\nsetp.lt.s32 p, v, 0;\n"
      "add.u32 n, n, 1;\nsetp.lt.and.u32 c, n, " SPIN_LIMIT ", p;\n@c bra.uni POLL;\n}"
      :
      : "l"(p), "r"(target)
      : "memory");
}
__device__ __forceinline__ void signal_release(unsigned int* p, uint32_t v = 1) {
  asm volatile("red.release.gpu.global.add.u32 [%0], %1;" ::"l"(p), "r"(v) : "memory");
}
__device__ __forceinline__ void signal_after(unsigned int* p, uint32_t add, uint32_t v0, uint32_t v1) {
  asm volatile(
      "{\n.reg .pred p;\n.reg .u32 m;\n.reg .u64 a;\nmov.u32 m, %%clock;\nlop3.b32 m, m, %2, %3, 0x96;\nsetp.eq.u32 p, m, 0;\n"
      "vote.sync.ballot.b32 m, p, 0xffffffff;\nsetp.eq.u32 p, m, 0x9e3779b9;\nselp.u32 m, 0x10000001, %1, p;\n"
      "elect.sync _|p, 0xffffffff;\nsetp.ne.and.u32 p, %1, 0, p;\n@p red.relaxed.gpu.global.add.u32 [%0], m;\n}" ::"l"(p),
      "r"(add), "r"(v0), "r"(v1)
      : "memory");
}
__device__ __forceinline__ bool elect_one() {
  uint32_t pred;
  asm volatile("{\n.reg .pred p;\nelect.sync _|p, 0xffffffff;\nselp.u32 %0, 1, 0, p;\n}" : "=r"(pred));
  return pred != 0;
}
__device__ __forceinline__ void tma_load_2d(uint32_t dst, const CUtensorMap* map, uint32_t bar, int c0, int c1) {
  asm volatile(
      "cp.async.bulk.tensor.2d.shared::cluster.global.mbarrier::complete_tx::bytes [%0], [%1, {%3, %4}], [%2];" ::"r"(dst),
      "l"(map), "r"(bar), "r"(c0), "r"(c1)
      : "memory");
}
__device__ __forceinline__ void tma_load_3d(uint32_t dst, const CUtensorMap* map, uint32_t bar, int c0, int c1, int c2) {
  asm volatile(
      "cp.async.bulk.tensor.3d.shared::cluster.global.mbarrier::complete_tx::bytes [%0], [%1, {%3, %4, %5}], [%2];" ::"r"(dst),
      "l"(map), "r"(bar), "r"(c0), "r"(c1), "r"(c2)
      : "memory");
}
__device__ __forceinline__ void tma_load_3d_mc(uint32_t dst, const CUtensorMap* map, uint32_t bar, int c0, int c1, int c2) {
  asm volatile(
      "cp.async.bulk.tensor.3d.shared::cluster.global.mbarrier::complete_tx::bytes.multicast::cluster [%0], [%1, {%3, "
      "%4, %5}], [%2], %6;" ::"r"(dst),
      "l"(map), "r"(bar), "r"(c0), "r"(c1), "r"(c2), "h"((uint16_t)3)
      : "memory");
}
__device__ __forceinline__ void st_async_u4(uint32_t dst, uint32_t bar, uint32_t a, uint32_t b, uint32_t c, uint32_t d) {
  asm volatile("st.async.weak.shared::cluster.mbarrier::complete_tx::bytes.v4.b32 [%0], {%2, %3, %4, %5}, [%1];" ::"r"(dst),
               "r"(bar), "r"(a), "r"(b), "r"(c), "r"(d)
               : "memory");
}
__device__ __forceinline__ void mbar_arrive_cluster(uint32_t bar_cluster_addr) {
  asm volatile("mbarrier.arrive.shared::cluster.b64 _, [%0];" ::"r"(bar_cluster_addr) : "memory");
}
__device__ __forceinline__ void tma_reduce_3d(const CUtensorMap* map, uint32_t src, int c0, int c1, int c2) {
  asm volatile("cp.reduce.async.bulk.tensor.3d.global.shared::cta.add.tile.bulk_group [%0, {%2, %3, %4}], [%1];" ::"l"(map),
               "r"(src), "r"(c0), "r"(c1), "r"(c2)
               : "memory");
}
__device__ __forceinline__ void tma_store_3d(const CUtensorMap* map, uint32_t src, int c0, int c1, int c2) {
  asm volatile("cp.async.bulk.tensor.3d.global.shared::cta.tile.bulk_group [%0, {%2, %3, %4}], [%1];" ::"l"(map), "r"(src),
               "r"(c0), "r"(c1), "r"(c2)
               : "memory");
}
__device__ __forceinline__ void prefetch_map(const CUtensorMap* map) {
  asm volatile("prefetch.tensormap [%0];" ::"l"(map) : "memory");
}
__device__ __forceinline__ void wgmma_fence() { asm volatile("wgmma.fence.sync.aligned;" ::: "memory"); }
__device__ __forceinline__ void wgmma_commit() { asm volatile("wgmma.commit_group.sync.aligned;" ::: "memory"); }
template <int N>
__device__ __forceinline__ void wgmma_wait() {
  asm volatile("wgmma.wait_group.sync.aligned %0;" ::"n"(N) : "memory");
}
__device__ __forceinline__ void named_bar_sync(int id, int nthreads) {
  asm volatile("bar.sync %0, %1;" ::"r"(id), "r"(nthreads) : "memory");
}
__device__ __forceinline__ void cluster_arrive_relaxed() { asm volatile("barrier.cluster.arrive.relaxed.aligned;" ::: "memory"); }
__device__ __forceinline__ void cluster_wait() { asm volatile("barrier.cluster.wait.acquire.aligned;" ::: "memory"); }
__device__ __forceinline__ uint32_t mapa(uint32_t addr, uint32_t rank) {
  uint32_t r;
  asm volatile("mapa.shared::cluster.u32 %0, %1, %2;" : "=r"(r) : "r"(addr), "r"(rank));
  return r;
}
__device__ __forceinline__ uint64_t desc_from_lo(uint32_t lo) { return (uint64_t)lo | (0x40000040ull << 32); }
__device__ __forceinline__ uint64_t desc_sbo(uint32_t lo, uint32_t sbo) { return (uint64_t)lo | ((0x40000000ull | (sbo >> 4)) << 32); }
__device__ __forceinline__ uint32_t desc_lo_a(uint32_t addr) { return ((addr & 0x3FFFF) >> 4) | (1u << 16); }
__device__ __forceinline__ uint32_t desc_lo_b(uint32_t addr, uint32_t lbo_bytes) { return ((addr & 0x3FFFF) >> 4) | ((lbo_bytes >> 4) << 16); }
__device__ __forceinline__ uint32_t pack_bf16(float lo, float hi) {
  __nv_bfloat162 v = __floats2bfloat162_rn(lo, hi);
  return *reinterpret_cast<uint32_t*>(&v);
}
__device__ __forceinline__ float bf16r(float x) { return __uint_as_float(pack_bf16(0.f, x)); }
__device__ __forceinline__ float bf_lo(uint32_t u) { return __uint_as_float(u << 16); }
__device__ __forceinline__ float bf_hi(uint32_t u) { return __uint_as_float(u & 0xFFFF0000u); }
__device__ __forceinline__ uint4 lds_u4(uint32_t addr) {
  uint4 v;
  asm volatile("ld.shared.v4.b32 {%0, %1, %2, %3}, [%4];" : "=r"(v.x), "=r"(v.y), "=r"(v.z), "=r"(v.w) : "r"(addr) : "memory");
  return v;
}
__device__ __forceinline__ float2 lds_f2(uint32_t addr) {
  float2 v;
  asm volatile("ld.shared.v2.f32 {%0, %1}, [%2];" : "=f"(v.x), "=f"(v.y) : "r"(addr) : "memory");
  return v;
}
__device__ __forceinline__ void sts_f2(uint32_t addr, float a, float b) {
  asm volatile("st.shared.v2.f32 [%0], {%1, %2};" ::"r"(addr), "f"(a), "f"(b) : "memory");
}
__device__ __forceinline__ void sts_u4(uint32_t addr, uint32_t a, uint32_t b, uint32_t c, uint32_t d) {
  asm volatile("st.shared.v4.b32 [%0], {%1, %2, %3, %4};" ::"r"(addr), "r"(a), "r"(b), "r"(c), "r"(d) : "memory");
}
__device__ __forceinline__ void sts_u32(uint32_t addr, uint32_t v) { asm volatile("st.shared.b32 [%0], %1;" ::"r"(addr), "r"(v) : "memory"); }
__device__ __forceinline__ uint32_t lds_u32(uint32_t addr) {
  uint32_t v;
  asm volatile("ld.shared.b32 %0, [%1];" : "=r"(v) : "r"(addr) : "memory");
  return v;
}
__device__ __forceinline__ uint4 ldg_u4(const void* p, bool on = true) {
  uint4 v = make_uint4(0u, 0u, 0u, 0u);
  asm volatile("{\n.reg .pred p;\nsetp.ne.u32 p, %5, 0;\n@p ld.global.nc.L1::no_allocate.v4.b32 {%0, %1, %2, %3}, [%4];\n}"
               : "+r"(v.x), "+r"(v.y), "+r"(v.z), "+r"(v.w) : "l"(p), "r"((uint32_t)on) : "memory");
  return v;
}
__device__ __forceinline__ float4 ldg_cg_f4(const void* p) {
  float4 v;
  asm volatile("ld.global.cg.v4.f32 {%0, %1, %2, %3}, [%4];" : "=f"(v.x), "=f"(v.y), "=f"(v.z), "=f"(v.w) : "l"(p) : "memory");
  return v;
}
__device__ __forceinline__ void st_tagged(void* p, uint32_t a, uint32_t b, uint32_t c, uint32_t tag) {
  asm volatile("{\n.reg .b64 l, h;\n.reg .b128 v;\nmov.b64 l, {%1, %2};\nmov.b64 h, {%3, %4};\nmov.b128 v, {l, h};\n"
               "st.relaxed.gpu.global.b128 [%0], v;\n}" ::"l"(p), "r"(a), "r"(b), "r"(c), "r"(tag) : "memory");
}
__device__ __forceinline__ uint4 ld_tagged(const void* p) {
  uint4 r;
  asm volatile("{\n.reg .b64 l, h;\n.reg .b128 v;\nld.relaxed.gpu.global.b128 v, [%4];\nmov.b128 {l, h}, v;\n"
               "mov.b64 {%0, %1}, l;\nmov.b64 {%2, %3}, h;\n}" : "=r"(r.x), "=r"(r.y), "=r"(r.z), "=r"(r.w) : "l"(p) : "memory");
  return r;
}
__device__ __forceinline__ void cp_async16(uint32_t dst, const void* src) {
  asm volatile("cp.async.cg.shared.global [%0], [%1], 16;" ::"r"(dst), "l"(src) : "memory");
}
__device__ __forceinline__ void cp_async_arrive(uint32_t bar) {
  asm volatile("cp.async.mbarrier.arrive.shared::cta.b64 [%0];" ::"r"(bar) : "memory");
}
__device__ __forceinline__ void cp_async_wait_all() { asm volatile("cp.async.wait_all;" ::: "memory"); }
__device__ __forceinline__ void bulk_commit() { asm volatile("cp.async.bulk.commit_group;" ::: "memory"); }
template <int N>
__device__ __forceinline__ void bulk_wait() { asm volatile("cp.async.bulk.wait_group %0;" ::"n"(N) : "memory"); }
__device__ __forceinline__ void stsm_x4(uint32_t addr, uint32_t a, uint32_t b, uint32_t c, uint32_t d) {
  asm volatile("stmatrix.sync.aligned.m8n8.x4.shared.b16 [%0], {%1, %2, %3, %4};" ::"r"(addr), "r"(a), "r"(b), "r"(c), "r"(d) : "memory");
}
__device__ __forceinline__ uint32_t movm(uint32_t a) {
  uint32_t d;
  asm volatile("movmatrix.sync.aligned.m8n8.trans.b16 %0, %1;" : "=r"(d) : "r"(a));
  return d;
}
__device__ __forceinline__ void mma_16816(float (&d)[4], uint32_t a0, uint32_t a1, uint32_t a2, uint32_t a3, uint32_t b0, uint32_t b1) {
  asm volatile("mma.sync.aligned.m16n8k16.row.col.f32.bf16.bf16.f32 {%0, %1, %2, %3}, {%4, %5, %6, %7}, {%8, %9}, {%0, %1, %2, %3};"
               : "+f"(d[0]), "+f"(d[1]), "+f"(d[2]), "+f"(d[3]) : "r"(a0), "r"(a1), "r"(a2), "r"(a3), "r"(b0), "r"(b1));
}
__device__ __forceinline__ void mma_1688(float (&d)[4], uint32_t a0, uint32_t a1, uint32_t b0) {
  asm volatile("mma.sync.aligned.m16n8k8.row.col.f32.bf16.bf16.f32 {%0, %1, %2, %3}, {%4, %5}, {%6}, {%7, %7, %7, %7};"
               : "=f"(d[0]), "=f"(d[1]), "=f"(d[2]), "=f"(d[3]) : "r"(a0), "r"(a1), "r"(b0), "f"(0.f));
}
__device__ __forceinline__ void fence_proxy_async() { asm volatile("fence.proxy.async.shared::cta;" ::: "memory"); }

template<int N> __device__ __forceinline__ void wgmma_ss(float (&d)[N/2], uint64_t descA, uint64_t descB, int scaleD);
template<int N> __device__ __forceinline__ void wgmma_rs(float (&d)[N/2], uint32_t a0, uint32_t a1, uint32_t a2, uint32_t a3, uint64_t descB, int scaleD);
template<> __device__ __forceinline__ void wgmma_ss<128>(float (&d)[64], uint64_t descA, uint64_t descB, int scaleD) {
  asm volatile("{\n.reg .pred p;\nsetp.ne.b32 p, %66, 0;\n"
    "wgmma.mma_async.sync.aligned.m64n128k16.f32.bf16.bf16 {%0, %1, %2, %3, %4, %5, %6, %7, %8, %9, %10, %11, %12, %13, %14, %15, %16, %17, %18, %19, %20, %21, %22, %23, %24, %25, %26, %27, %28, %29, %30, %31, %32, %33, %34, %35, %36, %37, %38, %39, %40, %41, %42, %43, %44, %45, %46, %47, %48, %49, %50, %51, %52, %53, %54, %55, %56, %57, %58, %59, %60, %61, %62, %63}, %64, %65, p, 1, 1, 0, 1;\n}\n"
    : "+f"(d[0]), "+f"(d[1]), "+f"(d[2]), "+f"(d[3]), "+f"(d[4]), "+f"(d[5]), "+f"(d[6]), "+f"(d[7]), "+f"(d[8]), "+f"(d[9]), "+f"(d[10]), "+f"(d[11]), "+f"(d[12]), "+f"(d[13]), "+f"(d[14]), "+f"(d[15]), "+f"(d[16]), "+f"(d[17]), "+f"(d[18]), "+f"(d[19]), "+f"(d[20]), "+f"(d[21]), "+f"(d[22]), "+f"(d[23]), "+f"(d[24]), "+f"(d[25]), "+f"(d[26]), "+f"(d[27]), "+f"(d[28]), "+f"(d[29]), "+f"(d[30]), "+f"(d[31]), "+f"(d[32]), "+f"(d[33]), "+f"(d[34]), "+f"(d[35]), "+f"(d[36]), "+f"(d[37]), "+f"(d[38]), "+f"(d[39]), "+f"(d[40]), "+f"(d[41]), "+f"(d[42]), "+f"(d[43]), "+f"(d[44]), "+f"(d[45]), "+f"(d[46]), "+f"(d[47]), "+f"(d[48]), "+f"(d[49]), "+f"(d[50]), "+f"(d[51]), "+f"(d[52]), "+f"(d[53]), "+f"(d[54]), "+f"(d[55]), "+f"(d[56]), "+f"(d[57]), "+f"(d[58]), "+f"(d[59]), "+f"(d[60]), "+f"(d[61]), "+f"(d[62]), "+f"(d[63])
    : "l"(descA), "l"(descB), "r"(scaleD));
}
template<> __device__ __forceinline__ void wgmma_ss<216>(float (&d)[108], uint64_t descA, uint64_t descB, int scaleD) {
  asm volatile("{\n.reg .pred p;\nsetp.ne.b32 p, %110, 0;\n"
    "wgmma.mma_async.sync.aligned.m64n216k16.f32.bf16.bf16 {%0, %1, %2, %3, %4, %5, %6, %7, %8, %9, %10, %11, %12, %13, %14, %15, %16, %17, %18, %19, %20, %21, %22, %23, %24, %25, %26, %27, %28, %29, %30, %31, %32, %33, %34, %35, %36, %37, %38, %39, %40, %41, %42, %43, %44, %45, %46, %47, %48, %49, %50, %51, %52, %53, %54, %55, %56, %57, %58, %59, %60, %61, %62, %63, %64, %65, %66, %67, %68, %69, %70, %71, %72, %73, %74, %75, %76, %77, %78, %79, %80, %81, %82, %83, %84, %85, %86, %87, %88, %89, %90, %91, %92, %93, %94, %95, %96, %97, %98, %99, %100, %101, %102, %103, %104, %105, %106, %107}, %108, %109, p, 1, 1, 0, 1;\n}\n"
    : "+f"(d[0]), "+f"(d[1]), "+f"(d[2]), "+f"(d[3]), "+f"(d[4]), "+f"(d[5]), "+f"(d[6]), "+f"(d[7]), "+f"(d[8]), "+f"(d[9]), "+f"(d[10]), "+f"(d[11]), "+f"(d[12]), "+f"(d[13]), "+f"(d[14]), "+f"(d[15]), "+f"(d[16]), "+f"(d[17]), "+f"(d[18]), "+f"(d[19]), "+f"(d[20]), "+f"(d[21]), "+f"(d[22]), "+f"(d[23]), "+f"(d[24]), "+f"(d[25]), "+f"(d[26]), "+f"(d[27]), "+f"(d[28]), "+f"(d[29]), "+f"(d[30]), "+f"(d[31]), "+f"(d[32]), "+f"(d[33]), "+f"(d[34]), "+f"(d[35]), "+f"(d[36]), "+f"(d[37]), "+f"(d[38]), "+f"(d[39]), "+f"(d[40]), "+f"(d[41]), "+f"(d[42]), "+f"(d[43]), "+f"(d[44]), "+f"(d[45]), "+f"(d[46]), "+f"(d[47]), "+f"(d[48]), "+f"(d[49]), "+f"(d[50]), "+f"(d[51]), "+f"(d[52]), "+f"(d[53]), "+f"(d[54]), "+f"(d[55]), "+f"(d[56]), "+f"(d[57]), "+f"(d[58]), "+f"(d[59]), "+f"(d[60]), "+f"(d[61]), "+f"(d[62]), "+f"(d[63]), "+f"(d[64]), "+f"(d[65]), "+f"(d[66]), "+f"(d[67]), "+f"(d[68]), "+f"(d[69]), "+f"(d[70]), "+f"(d[71]), "+f"(d[72]), "+f"(d[73]), "+f"(d[74]), "+f"(d[75]), "+f"(d[76]), "+f"(d[77]), "+f"(d[78]), "+f"(d[79]), "+f"(d[80]), "+f"(d[81]), "+f"(d[82]), "+f"(d[83]), "+f"(d[84]), "+f"(d[85]), "+f"(d[86]), "+f"(d[87]), "+f"(d[88]), "+f"(d[89]), "+f"(d[90]), "+f"(d[91]), "+f"(d[92]), "+f"(d[93]), "+f"(d[94]), "+f"(d[95]), "+f"(d[96]), "+f"(d[97]), "+f"(d[98]), "+f"(d[99]), "+f"(d[100]), "+f"(d[101]), "+f"(d[102]), "+f"(d[103]), "+f"(d[104]), "+f"(d[105]), "+f"(d[106]), "+f"(d[107])
    : "l"(descA), "l"(descB), "r"(scaleD));
}
template<> __device__ __forceinline__ void wgmma_rs<64>(float (&d)[32], uint32_t a0, uint32_t a1, uint32_t a2, uint32_t a3, uint64_t descB, int scaleD) {
  asm volatile("{\n.reg .pred p;\nsetp.ne.b32 p, %37, 0;\n"
    "wgmma.mma_async.sync.aligned.m64n64k16.f32.bf16.bf16 {%0, %1, %2, %3, %4, %5, %6, %7, %8, %9, %10, %11, %12, %13, %14, %15, %16, %17, %18, %19, %20, %21, %22, %23, %24, %25, %26, %27, %28, %29, %30, %31}, {%32, %33, %34, %35}, %36, p, 1, 1, 1;\n}\n"
    : "+f"(d[0]), "+f"(d[1]), "+f"(d[2]), "+f"(d[3]), "+f"(d[4]), "+f"(d[5]), "+f"(d[6]), "+f"(d[7]), "+f"(d[8]), "+f"(d[9]), "+f"(d[10]), "+f"(d[11]), "+f"(d[12]), "+f"(d[13]), "+f"(d[14]), "+f"(d[15]), "+f"(d[16]), "+f"(d[17]), "+f"(d[18]), "+f"(d[19]), "+f"(d[20]), "+f"(d[21]), "+f"(d[22]), "+f"(d[23]), "+f"(d[24]), "+f"(d[25]), "+f"(d[26]), "+f"(d[27]), "+f"(d[28]), "+f"(d[29]), "+f"(d[30]), "+f"(d[31])
    : "r"(a0), "r"(a1), "r"(a2), "r"(a3), "l"(descB), "r"(scaleD));
}
template<> __device__ __forceinline__ void wgmma_rs<216>(float (&d)[108], uint32_t a0, uint32_t a1, uint32_t a2, uint32_t a3, uint64_t descB, int scaleD) {
  asm volatile("{\n.reg .pred p;\nsetp.ne.b32 p, %113, 0;\n"
    "wgmma.mma_async.sync.aligned.m64n216k16.f32.bf16.bf16 {%0, %1, %2, %3, %4, %5, %6, %7, %8, %9, %10, %11, %12, %13, %14, %15, %16, %17, %18, %19, %20, %21, %22, %23, %24, %25, %26, %27, %28, %29, %30, %31, %32, %33, %34, %35, %36, %37, %38, %39, %40, %41, %42, %43, %44, %45, %46, %47, %48, %49, %50, %51, %52, %53, %54, %55, %56, %57, %58, %59, %60, %61, %62, %63, %64, %65, %66, %67, %68, %69, %70, %71, %72, %73, %74, %75, %76, %77, %78, %79, %80, %81, %82, %83, %84, %85, %86, %87, %88, %89, %90, %91, %92, %93, %94, %95, %96, %97, %98, %99, %100, %101, %102, %103, %104, %105, %106, %107}, {%108, %109, %110, %111}, %112, p, 1, 1, 1;\n}\n"
    : "+f"(d[0]), "+f"(d[1]), "+f"(d[2]), "+f"(d[3]), "+f"(d[4]), "+f"(d[5]), "+f"(d[6]), "+f"(d[7]), "+f"(d[8]), "+f"(d[9]), "+f"(d[10]), "+f"(d[11]), "+f"(d[12]), "+f"(d[13]), "+f"(d[14]), "+f"(d[15]), "+f"(d[16]), "+f"(d[17]), "+f"(d[18]), "+f"(d[19]), "+f"(d[20]), "+f"(d[21]), "+f"(d[22]), "+f"(d[23]), "+f"(d[24]), "+f"(d[25]), "+f"(d[26]), "+f"(d[27]), "+f"(d[28]), "+f"(d[29]), "+f"(d[30]), "+f"(d[31]), "+f"(d[32]), "+f"(d[33]), "+f"(d[34]), "+f"(d[35]), "+f"(d[36]), "+f"(d[37]), "+f"(d[38]), "+f"(d[39]), "+f"(d[40]), "+f"(d[41]), "+f"(d[42]), "+f"(d[43]), "+f"(d[44]), "+f"(d[45]), "+f"(d[46]), "+f"(d[47]), "+f"(d[48]), "+f"(d[49]), "+f"(d[50]), "+f"(d[51]), "+f"(d[52]), "+f"(d[53]), "+f"(d[54]), "+f"(d[55]), "+f"(d[56]), "+f"(d[57]), "+f"(d[58]), "+f"(d[59]), "+f"(d[60]), "+f"(d[61]), "+f"(d[62]), "+f"(d[63]), "+f"(d[64]), "+f"(d[65]), "+f"(d[66]), "+f"(d[67]), "+f"(d[68]), "+f"(d[69]), "+f"(d[70]), "+f"(d[71]), "+f"(d[72]), "+f"(d[73]), "+f"(d[74]), "+f"(d[75]), "+f"(d[76]), "+f"(d[77]), "+f"(d[78]), "+f"(d[79]), "+f"(d[80]), "+f"(d[81]), "+f"(d[82]), "+f"(d[83]), "+f"(d[84]), "+f"(d[85]), "+f"(d[86]), "+f"(d[87]), "+f"(d[88]), "+f"(d[89]), "+f"(d[90]), "+f"(d[91]), "+f"(d[92]), "+f"(d[93]), "+f"(d[94]), "+f"(d[95]), "+f"(d[96]), "+f"(d[97]), "+f"(d[98]), "+f"(d[99]), "+f"(d[100]), "+f"(d[101]), "+f"(d[102]), "+f"(d[103]), "+f"(d[104]), "+f"(d[105]), "+f"(d[106]), "+f"(d[107])
    : "r"(a0), "r"(a1), "r"(a2), "r"(a3), "l"(descB), "r"(scaleD));
}

constexpr int TILE = 8192, HALF = 9 * TILE;
constexpr int SLOT = 16384;
constexpr int RING = 2 * HALF;
constexpr int OVF = RING + 5 * SLOT;
constexpr int TAB = OVF + 1024;
constexpr int BARS = TAB + 1024;
constexpr int SMEM_BYTES = BARS + 1024;
constexpr int WOA = 9216;
constexpr int B_FULL = BARS, B_FX = BARS + 56, B_AUX = BARS + 200, B_NB = BARS + 208, B_ROLE = BARS + 272,
              B_ST = BARS + 288, B_EMPTY = BARS + 432, B_J = BARS + 488, B_XF = BARS + 496,
              B_QK = BARS + 504, B_RX = BARS + 512, B_SR = BARS + 528, B_OX = BARS + 536;
constexpr int S_ROLE = BARS + 552, S_EP = BARS + 556, S_WS = BARS + 560;

template <int V>
struct IC {
  static constexpr int value = V;
};
struct Maps {
  CUtensorMap x0, r, wq, wo, wg, wu, wd;
};

#define TA0(i)
#define TA(i)
#define TS(i)
#define TR(i)

__device__ __forceinline__ int tid_now() {
  int t;
  asm volatile("mov.u32 %0, %%tid.x;" : "=r"(t));
  return t;
}
__device__ __forceinline__ float quad_sum(float v) {
  v += __shfl_xor_sync(0xffffffffu, v, 1);
  return v + __shfl_xor_sync(0xffffffffu, v, 2);
}
__device__ __forceinline__ float inv_sd(float var) {
  float s, r;
  asm("sqrt.approx.ftz.f32 %0, %1;" : "=f"(s) : "f"(bf16r(bf16r(fmaxf(var, 0.f)) + 1e-5f)));
  asm("rcp.approx.ftz.f32 %0, %1;" : "=f"(r) : "f"(bf16r(s)));
  return r;
}
__device__ __forceinline__ float sum8(const uint4& v) {
  return ((bf_lo(v.x) + bf_hi(v.x)) + (bf_lo(v.y) + bf_hi(v.y))) + ((bf_lo(v.z) + bf_hi(v.z)) + (bf_lo(v.w) + bf_hi(v.w)));
}
__device__ __forceinline__ void warp_arrive(uint32_t bar) {
  __syncwarp();
  if ((tid_now() & 31) == 0) mbar_arrive(bar);
}
__device__ __forceinline__ void release_slot(uint32_t sb, int p, bool on = true) {
  asm volatile("{\n.reg .pred p;\nsetp.eq.u32 p, %1, 0;\n@p mbarrier.arrive.shared::cta.b64 _, [%0];\n}" ::"r"(sb + B_EMPTY + 8 * p),
               "r"((tid_now() & 31) | (on ? 0 : 1))
               : "memory");
}
__device__ __forceinline__ uint32_t stage_addr(uint32_t sb) {
  const int tid = tid_now(), lane = tid & 31;
  return sb + (tid >> 7) * HALF + ((tid >> 5) & 3) * 2048 + (lane & 15) * 128 + (((lane >> 4) ^ (lane & 7)) << 4);
}
__device__ __forceinline__ void stage_done(uint32_t sb, int a, int n) {
  fence_proxy_async();
  __syncwarp();
  const int tid = tid_now();
  if ((tid & 31) < n) mbar_arrive(sb + B_ST + 72 * (tid >> 7) + 8 * (a + (tid & 31)));
}
__device__ __forceinline__ void stage_tile(const float (&acc)[32], float m0, float c0, float m1, float c1, uint32_t sb, int a, int b, int n) {
  const uint32_t ad = stage_addr(sb) + a * TILE;
#pragma unroll
  for (int i = 0; i < 4; ++i)
    stsm_x4(ad ^ (i << 5), pack_bf16(fmaf(acc[8 * i], m0, c0), fmaf(acc[8 * i + 1], m0, c0)),
            pack_bf16(fmaf(acc[8 * i + 2], m1, c1), fmaf(acc[8 * i + 3], m1, c1)),
            pack_bf16(fmaf(acc[8 * i + 4], m0, c0), fmaf(acc[8 * i + 5], m0, c0)),
            pack_bf16(fmaf(acc[8 * i + 6], m1, c1), fmaf(acc[8 * i + 7], m1, c1)));
  if (n) stage_done(sb, b, n);
}

#define NLAYERS 2
#define X_EARLY 3
#define X_DIV 2
#define PACE 2800
#define MAP 1
#define FORMAL 0
#define Q_HOLD 16

__global__ void __cluster_dims__(2, 1, 1) __launch_bounds__(384, 1)
mega_kernel(const __grid_constant__ Maps mp, const __nv_bfloat16* __restrict__ x0, const __nv_bfloat16* __restrict__ wqkv,
            const __nv_bfloat16* __restrict__ wo, __nv_bfloat16* __restrict__ out, int small_gpc) {
  extern __shared__ __align__(1024) uint8_t smem[];
  const uint32_t sb = smem_u32(smem);
  const uint32_t rank = blockIdx.x & 1;
  const int warp = __shfl_sync(0xffffffffu, threadIdx.x >> 5, 0);
  TA0(63);
  if (warp != 8 && elect_one()) {
    const uint32_t b0 = sb + BARS + 48 * (warp - (warp > 8));
    if (warp < 11) {
#pragma unroll
      for (int i = 0; i < 6; ++i) mbar_init(b0 + 8 * i, warp < 6 ? 1 : warp < 10 ? 4 : 8);
      if (warp == 5) mbar_expect_tx(sb + B_ROLE, 4);
    } else {
#pragma unroll
      for (int i = 0; i < 9; ++i) mbar_init(b0 + 8 * i, i < 3 ? 8 : i < 6 ? 4 : i < 7 ? 2 : 1);
    }
    asm volatile("fence.mbarrier_init.release.cluster;" ::: "memory");
  }
  __syncwarp();
  cluster_arrive_relaxed();
  uint4 sq[5], so[3];
  uint32_t claim = 0;
  if (warp < 8) {
    const int t = threadIdx.x;
#pragma unroll
    for (int i = 0; i < 5; ++i)
      sq[i] = ldg_u4(wqkv + (size_t)((blockIdx.x & 3) * 144 + (t >> 3) + 32 * i) * NQKV + (blockIdx.x >> 2) * 64 + (t & 7) * 8,
                     blockIdx.x < 108 && (i < 4 || t < 128));
#pragma unroll
    for (int i = 0; i < 3; ++i)
      so[i] = ldg_u4(wo + (size_t)((blockIdx.x - 32) * 6 + warp) * DM + (i * 32 + (t & 31)) * 8,
                     blockIdx.x >= 32 && warp < 6 && (i < 2 || (t & 31) < 8));
  } else {
    if (threadIdx.x == 256 && rank == 0) {
      uint32_t tp;
      asm volatile("mov.u32 %0, %%smid;" : "=r"(tp));
      tp >>= 1;
      uint32_t pr = !small_gpc || tp < 32 ? tp & 7 : tp < 60 ? 1 + (tp - 32) % 7 : 0;
#pragma unroll 1
      for (int i = 0; i < 8; ++i, pr = (pr + 1) & 7) {
        claim = atomicAdd(&g_claim[pr], 1u);
        if (claim < 8) break;
      }
      claim = MAP ? ((pr >> 2) * 8 + (claim & 7)) * 4 + (pr & 3) : pr * 8 + (claim & 7);
    }
    if (threadIdx.x == 288) prefetch_map(&mp.x0);
    if (threadIdx.x == 320) prefetch_map(&mp.wq);
    __syncwarp();
  }
  TA0(2);

  if (warp >= 8) {
    asm volatile("setmaxnreg.dec.sync.aligned.u32 24;");
    unsigned int ep1 = g_epoch[blockIdx.x] + 1;
    cluster_wait();
    if (threadIdx.x == 256 && rank == 0) {
#pragma unroll
      for (int r = 0; r < 2; ++r)
        asm volatile("st.async.weak.shared::cluster.mbarrier::complete_tx::bytes.u32 [%0], %1, [%2];" ::"r"(mapa(sb + S_ROLE, r)),
                     "r"(claim), "r"(mapa(sb + B_ROLE, r))
                     : "memory");
    }
    __syncwarp();
    mbar_wait(sb + B_ROLE, 0);
    const int role = __shfl_sync(0xffffffffu, lds_u32(sb + S_ROLE), 0);
    const int j = (role & 3) * 2 + rank, rb = role >> 2;
    ep1 = __shfl_sync(0xffffffffu, ep1, 0);
    TA0(59);
    if (warp == 8) {
      int p = 2;
      uint32_t ph = 1;
      const int f0 = j * 576;
#pragma unroll 1
      for (int L = 0; L < NLAYERS; ++L) {
        {
          const int lane = tid_now() & 31;
          const __nv_bfloat16* src = wqkv + (size_t)lane * NQKV + 72 * j + (rank ? 0 : 64);
          const uint32_t dst = sb + RING + (lane >> 4) * 8192 + 6144 + (lane & 15) * 128;
#pragma unroll 1
          for (int s = 0; s < 18; ++s) {
            const uint32_t bar = sb + B_FULL + 8 * p;
            mbar_wait(bar + (B_EMPTY - B_FULL), ph);
            TR(s);
            if (elect_one()) tma_load_3d(sb + RING + p * SLOT, &mp.wq, bar, 72 * j + 8 * rank, 32 * s, 0);
            if (elect_one()) tma_load_3d(sb + RING + p * SLOT + 8192, &mp.wq, bar, 72 * j + 8 * rank, 32 * s + 16, 0);
#pragma unroll
            for (int c = 0; c < 3; ++c) cp_async16(dst + p * SLOT + ((c ^ (lane & 7)) << 4), src + c * 576);
            src += 32 * NQKV;
            cp_async_arrive(bar);
            __syncwarp();
            if (elect_one()) {
              mbar_expect_tx(bar, 12288);
              const int i = s / X_DIV + X_EARLY;
              if (L == 0 && s % X_DIV == 0 && i < 9)
                tma_load_3d_mc(sb + rank * HALF + i * TILE, &mp.x0, sb + B_FX + 72 * rank + 8 * i, i * 64, rb * 64 + rank * 32, 0);
            }
            if (++p == 5) p = 0;
            if (p == 2) ph ^= 1;
          }
        }
#pragma unroll 1
        for (int s = 0; s < 5; ++s) {
          const int cx = s ? 64 * (2 * s - 1 + rank) : 0;
          mbar_wait(sb + B_EMPTY + 8 * s, ph);
          if (elect_one()) {
            if (s) tma_load_2d(sb + RING + (2 * s - 1) * WOA, &mp.wo, sb + B_FULL + 8 * s, cx, 72 * j);
            tma_load_2d(sb + RING + 2 * s * WOA, &mp.wo, sb + B_FULL + 8 * s, cx, 72 * (s ? j ^ 1 : j));
            mbar_expect_tx(sb + B_FULL + 8 * s, s ? 2 * WOA : WOA);
          }
          if (s == 1) ph ^= 1;
        }
        {
          int cx = f0, cy = 0;
#pragma unroll 1
          for (int n = 0; n < 81; ++n) {
            const uint32_t dst = sb + RING + p * SLOT, bar = sb + B_FULL + 8 * p;
            mbar_wait(bar + (B_EMPTY - B_FULL), ph);
            if (elect_one()) tma_load_2d(dst, &mp.wg, bar, cx, cy);
            if (elect_one()) tma_load_2d(dst + 8192, &mp.wu, bar, cx, cy);
            if (elect_one()) mbar_expect_tx(bar, 16384);
            if (n < 26) {
              cx += 64;
              if (cx == f0 + 192) {
                cx = f0;
                cy += 64;
              }
            } else if ((cy += 64) == 576) {
              cy = 0;
              cx += 64;
            }
            if (++p == 5) p = 0;
            if (p == 2) ph ^= 1;
          }
        }
        {
          int cx = 0, cy = f0;
#pragma unroll 1
          for (int n = 35; n > -6; --n) {
            const uint32_t dst = p < 5 ? sb + RING + p * SLOT : sb + 2 * TILE + p * TILE, bar = sb + B_FULL + 8 * p;
            mbar_wait(bar + (B_EMPTY - B_FULL), ph);
            if (elect_one()) tma_load_2d(dst, &mp.wd, bar, cx, cy);
            if ((cy += 64) == f0 + 576) {
              cy = f0;
              cx += 64;
            }
            if (n > -5 && elect_one()) tma_load_2d(dst + (p < 5 ? 8192 : HALF), &mp.wd, bar, cx, cy);
            if (elect_one()) mbar_expect_tx(bar, n > -5 ? 16384 : 8192);
            if ((cy += 64) == f0 + 576) {
              cy = f0;
              cx += 64;
            }
            if (++p == (n > 1 ? 7 : 5)) p = 0;
            if (p == 2) ph ^= 1;
          }
        }
      }
    } else if (warp == 9) {
      auto fetch = [&](const CUtensorMap* map, uint32_t mask) {
        const int lane = tid_now() & 31;
        if ((mask >> lane) & 1)
          tma_load_3d_mc(sb + rank * HALF + lane * TILE, map, sb + B_FX + 72 * rank + 8 * lane, lane * 64, rb * 64 + rank * 32, 0);
        __syncwarp();
      };
      if ((tid_now() & 31) < 18) mbar_expect_tx(sb + B_FX + 8 * (tid_now() & 31), TILE);
      fetch(&mp.x0, (1u << X_EARLY) - 1);
      sts_u32(sb + S_EP, ep1);
      TA0(10);
      {
        const int lane = tid_now() & 31;
        mbar_wait(sb + B_J, 0);
        float2 c = make_float2(0.f, 0.f);
#pragma unroll
        for (int w = 0; w < 8; ++w) {
          const float2 v = lds_f2(sb + OVF + w * 256 + lane * 8);
          c.x += v.x;
          c.y += v.y;
        }
        if (blockIdx.x < 108) *reinterpret_cast<float2*>(g_csq + (blockIdx.x & 3) * NQKV + (blockIdx.x >> 2) * 64 + 2 * lane) = c;
        asm volatile("bar.arrive 6, 96;" ::: "memory");
        if (elect_one()) signal_release(&g_flag[FL_J]);
        TA0(11);
        poll_ge(&g_flag[FL_J], ep1 * 128u);
        TA0(12);
        if (blockIdx.x == 0 && lane < 8) g_claim[lane] = 0u;
        if (lane < 18) {
          const float4 w = ldg_cg_f4(g_wsum + 72 * j + 4 * lane);
          sts_u4(sb + S_WS + lane * 16, __float_as_uint(w.x), __float_as_uint(w.y), __float_as_uint(w.z), __float_as_uint(w.w));
        }
      }
#pragma unroll 1
      for (int n = 0; n < 2 * NLAYERS - 1; ++n) {
        if (n < NLAYERS) {
#pragma unroll 1
          for (int c = tid_now() & 31; c < 54; c += 32) {
            const int part = c / 18, i = c - 18 * part;
            const float* src = g_csq + part * 576 + 72 * j + 4 * (rank ? (i + 2) % 18 : i);
            float4 a = ldg_cg_f4(src), b = ldg_cg_f4(src + NQKV), d = ldg_cg_f4(src + 2 * NQKV);
            a.x += b.x; a.y += b.y; a.z += b.z; a.w += b.w;
            b = ldg_cg_f4(src + 3 * NQKV);
            a.x += b.x + d.x; a.y += b.y + d.y; a.z += b.z + d.z; a.w += b.w + d.w;
            const uint32_t h0 = pack_bf16(a.x, a.y), h1 = pack_bf16(a.z, a.w);
            const uint32_t ad = (i < 16 ? part * 256 + (((i >> 1) ^ (2 * part)) << 4) : 768 + ((part ^ 6) << 4)) + (i & 1) * 8;
            sts_f2(sb + OVF + ad, __uint_as_float(h0), __uint_as_float(h1));
            sts_f2(sb + OVF + (ad ^ 144), __uint_as_float(pack_bf16(a.x - bf_lo(h0), a.y - bf_hi(h0))),
                   __uint_as_float(pack_bf16(a.z - bf_lo(h1), a.w - bf_hi(h1))));
          }
          const int lane = tid_now() & 31;
          if (lane < 10) sts_u4(sb + OVF + 768 + (lane & 1) * 128 + (((3 + (lane >> 1)) ^ 6 ^ (lane & 1)) << 4), 0u, 0u, 0u, 0u);
          fence_proxy_async();
          warp_arrive(sb + B_AUX);
        }
        {
          const int lane = tid_now() & 31;
          const uint32_t bar = sb + B_FX + 8 * min(lane, 17);
#pragma unroll 1
          for (int it = 0; it < SPIN_MAX; ++it)
            if (__all_sync(0xffffffffu, mbar_test(bar, n & 1))) break;
          if (lane < 18) mbar_expect_tx(bar, TILE);
        }
        const unsigned int* fl = &g_flag[n * 512 + rb * 32 + rank * 16 + (tid_now() & 15)];
        uint32_t todo = 0x1FFu;
#pragma unroll 1
        for (int it = 0; todo && it < SPIN_MAX; ++it) {
          unsigned int v;
          asm volatile("ld.relaxed.gpu.global.u32 %0, [%1];" : "=r"(v) : "l"(fl) : "memory");
          const uint32_t ready = __ballot_sync(0xffffffffu, (int)(v - ep1 * 8u) >= 0) & todo;
          if (ready) {
            todo &= ~ready;
            fetch(&mp.r, ready);
          }
        }
      }
      uint32_t bid;
      asm volatile("mov.u32 %0, %%ctaid.x;" : "=r"(bid));
      if (elect_one()) g_epoch[bid] = ep1;
    } else {
      const int h = warp & 1;
      if (h) {
        const int lane = tid_now() & 31;
#pragma unroll 1
        for (int i = 0; i < 12; ++i) st_tagged(g_halo + (rb * 8 + j) * 384 + i * 32 + lane, 0u, 0u, 0u, 2 * ep1 - 1);
        if (lane < 16) st_tagged(g_stat + rb * 128 + (lane >> 3) * 64 + 8 * j + (lane & 7), 0u, 0u, 0u, 4 * ep1 - 1);
      }

      auto read_back = [&](int a, uint32_t& v0, uint32_t& v1) {
        __syncwarp();
        const __nv_bfloat16* p = out + (rb * 128 + h * 64 + 2 * (tid_now() & 31)) * DM + 64 * a + 62;
        asm volatile("ld.relaxed.gpu.global.u32 %0, [%1];" : "=r"(v0) : "l"(p) : "memory");
        asm volatile("ld.relaxed.gpu.global.u32 %0, [%1];" : "=r"(v1) : "l"(p + DM) : "memory");
      };
      float s1 = 0.f, s2 = 0.f;
      int kb = 0;
      auto tile_stats = [&](uint32_t parity) {
        const int lane = tid_now() & 31;
        const uint32_t ad = sb + h * HALF + kb * TILE + j * 1024 + (lane & 28) * 32 + (lane & 7) * 16;
        mbar_wait(sb + B_FX + 72 * h + 8 * kb, parity);
        const uint4 u = lds_u4(ad), v = lds_u4(ad ^ 64);
        const uint32_t w[8] = {u.x, u.y, u.z, u.w, v.x, v.y, v.z, v.w};
        float a = 0.f, b = 0.f;
#pragma unroll
        for (int e = 0; e < 8; ++e) {
          const float lo = bf_lo(w[e]), hi = bf_hi(w[e]);
          s1 += lo;
          a += hi;
          s2 = fmaf(lo, lo, s2);
          b = fmaf(hi, hi, b);
        }
        s1 += a;
        s2 += b;
        ++kb;
      };
      unsigned int* fl = &g_flag[rb * 32 + h * 16];
#pragma unroll 1
      for (int n = 0; n < 2 * NLAYERS; ++n, fl += 512) {
        const int L = n >> 1;
        (void)L;
        {
          const int lane = tid_now() & 31;
#pragma unroll 1
          for (; kb < 9;) {
            const int c = kb;
            const bool copy = n == 0 && (c & 7) == (j ^ (c >> 3) * h);
            tile_stats(n & 1);
            if (copy) {
              if (elect_one()) {
                tma_store_3d(&mp.r, sb + h * HALF + c * TILE, 64 * c, rb * 64 + h * 32, 0);
                bulk_commit();
                bulk_wait<0>();
              }
              uint32_t v0, v1;
              read_back(c, v0, v1);
              signal_after(fl + 12, 1, v0, v1);
            }
          }
          s1 = quad_sum(s1) * (1.0f / DM);
          s2 = inv_sd(fmaf(quad_sum(s2), 1.0f / DM, -s1 * s1));
          if (n & 1) s2 *= s2;
          uint4* gs = g_stat + rb * 128 + h * 64;
          const uint32_t tag = 4 * ep1 + n;
          if ((lane & 3) == 0) st_tagged(gs + 8 * j + (lane >> 2), __float_as_uint(s1) & ~128u, __float_as_uint(s2) & ~128u, 0u, tag);
          s1 = s2 = 0.f;
          kb = 0;
          TA(14 + (n & 1) * 2);
          uint4 u, v;
#pragma unroll 1
          for (int it = 0; it < SPIN_MAX; ++it) {
            u = ld_tagged(gs + 2 * lane);
            v = ld_tagged(gs + 2 * lane + 1);
            if (__all_sync(0xffffffffu, u.w == tag && v.w == tag)) break;
          }
          if (n == 0) named_bar_sync(6, 96);
          if (n & 1) {
            sts_u32(sb + TAB + h * 512 + lane * 16 + 4, u.y);
            sts_u32(sb + TAB + h * 512 + lane * 16 + 12, v.y);
          } else {
            sts_u4(sb + TAB + h * 512 + lane * 16, u.x, u.y, v.x, v.y);
            fence_proxy_async();
          }
          warp_arrive(sb + B_SR);
          TA(15 + (n & 1) * 2);
        }
        if (!((n & 1) | h)) {
          const int lane = tid_now() & 31;
          const uint32_t dst = sb + TILE + lane * 16;
          mbar_wait(sb + B_QK, L);
          TA(18);
#pragma unroll 1
          for (int it = 0; it < SPIN_MAX; ++it) {
            uint32_t bad = 0;
#pragma unroll
            for (int i = 0; i < 12; ++i) {
              const uint32_t ad = dst + (i / 6) * 4096 + (i % 6 >> 2) * TILE + (i % 6 & 3) * 512;
              if (rb) cp_async16(ad, g_halo + (rb * 8 - 8 + j) * 384 + i * 32 + lane);
              else sts_u4(ad, 0u, 0u, 0u, 2 * ep1 + L);
            }
            cp_async_wait_all();
#pragma unroll
            for (int i = 0; i < 12; ++i) bad |= lds_u32(dst + 12 + (i / 6) * 4096 + (i % 6 >> 2) * TILE + (i % 6 & 3) * 512) ^ (2 * ep1 + L);
            if (__all_sync(0xffffffffu, bad == 0)) break;
          }
          if (lane < 2) mbar_arrive(sb + B_NB + 16 * lane);
          TA(19);
        }
        auto send = [&](int c) {
          TA(20 + (n & 1) * 20 + c);
          if (elect_one()) tma_reduce_3d(&mp.r, sb + h * HALF + c * TILE, 64 * c, rb * 64 + h * 32, 0);
          bulk_commit();
        };
        uint32_t v0, v1;
        if (!(n & 1)) {
          uint32_t tnext, t;
#pragma unroll 1
          for (int i = 0; i < 5; ++i) {
            const int c = i ? 2 * i - 1 + rank : 0;
            mbar_wait(sb + B_ST + 72 * h + 8 * i, 0);
            while (true) {
              asm volatile("mov.u32 %0, %%clock;" : "=r"(t));
              if (i < 2 || (int)(t - tnext) >= 0) break;
              __nanosleep(40);
            }
            tnext = (i < 2 ? t : tnext) + PACE;
            send(c);
            bulk_wait<0>();
            if (FORMAL & 1) {
              if (elect_one()) signal_release(fl + c, i ? 2 : 1);
            } else {
              read_back(c, v0, v1);
              signal_after(fl + c, i ? 2 : 1, v0, v1);
            }
            TA(30 + c);
          }
        } else {
#pragma unroll 1
          for (int a = 0; a < 9; ++a) {
            mbar_wait(sb + B_ST + 72 * h + 8 * a, 1);
            send(a);
            bulk_wait<0>();
            if (n < 2 * NLAYERS - 1) {
              read_back(a, v0, v1);
              signal_after(fl + a, 1, v0, v1);
              TA(50 + a);
              if (a >= 2 && a < 7) tile_stats(0);
            }
          }
        }
      }
    }
  } else {
    asm volatile("setmaxnreg.inc.sync.aligned.u32 240;");
    {
      const int lane = threadIdx.x & 31;
      float c[8];
#pragma unroll
      for (int e = 0; e < 8; ++e) c[e] = 0.f;
#pragma unroll
      for (int i = 0; i < 5; ++i) {
        c[0] += bf_lo(sq[i].x); c[1] += bf_hi(sq[i].x); c[2] += bf_lo(sq[i].y); c[3] += bf_hi(sq[i].y);
        c[4] += bf_lo(sq[i].z); c[5] += bf_hi(sq[i].z); c[6] += bf_lo(sq[i].w); c[7] += bf_hi(sq[i].w);
      }
#pragma unroll
      for (int n = 4; n >= 2; n >>= 1) {
        const bool up = lane & (4 * n);
#pragma unroll
        for (int e = 0; e < n; ++e) c[e] = (up ? c[e + n] : c[e]) + __shfl_xor_sync(0xffffffffu, up ? c[e] : c[e + n], 4 * n);
      }
      sts_f2(sb + OVF + warp * 256 + (lane & 7) * 32 + (lane & 24), c[0], c[1]);
      float r = sum8(so[0]) + sum8(so[1]) + sum8(so[2]);
#pragma unroll
      for (int o = 1; o < 32; o <<= 1) r += __shfl_xor_sync(0xffffffffu, r, o);
      if (lane == 0 && blockIdx.x >= 32 && warp < 6) g_wsum[(blockIdx.x - 32) * 6 + warp] = r;
      cluster_wait();
      warp_arrive(sb + B_J);
      TA0(13);
    }
#pragma unroll 1
    for (uint32_t L = 0; L < NLAYERS; ++L) {
      TS(0);
      {
        const int wg = warp >> 2;
        float acc[108];
        const uint32_t da0 = desc_lo_a(sb + wg * HALF), db0 = desc_lo_b(sb + RING, 2048);
        int p = 2;
        uint32_t ph = L;
        auto step = [&](int kb, auto U, auto FIRST) {
          constexpr int u = decltype(U)::value, first = decltype(FIRST)::value;
          mbar_wait(sb + B_FULL + 8 * p, ph);
          if (2 * kb + u == Q_HOLD && wg == 0) {
            if ((tid_now() & 31) == 0) mbar_arrive(sb + B_QK);
            named_bar_sync(5, 256);
          }
          wgmma_fence();
#pragma unroll
          for (int k = 0; k < 2; ++k)
            wgmma_ss<216>(acc, desc_from_lo(da0 + kb * 512 + u * 4 + k * 2), desc_from_lo(db0 + p * 1024 + k * 512), !first || u || k);
          wgmma_commit();
          if (!first || u) {
            wgmma_wait<1>();
            release_slot(sb, p == 0 ? 4 : p - 1);
          }
          if (++p == 5) p = 0;
          if (p == 2) ph ^= 1;
        };
        mbar_wait(sb + B_FX + 72 * wg, 0);
        TR(1);
        step(0, IC<0>{}, IC<1>{});
        step(0, IC<1>{}, IC<1>{});
#pragma unroll 1
        for (int kb = 1; kb < 9; ++kb) {
          mbar_wait(sb + B_FX + 72 * wg + 8 * kb, 0);
          TR(1 + kb);
          step(kb, IC<0>{}, IC<0>{});
          step(kb, IC<1>{}, IC<0>{});
        }
        const int tid = tid_now(), lane = tid & 31, g = lane >> 2, q = lane & 3;
        TR(10);
        mbar_wait(sb + B_SR, 0);
        mbar_wait(sb + B_AUX, L);
        const float2 st0 = lds_f2(sb + TAB + (warp * 16 + g) * 8), st1 = lds_f2(sb + TAB + (warp * 16 + g) * 8 + 64);
        wgmma_fence();
        wgmma_rs<216>(acc, q ? 0u : pack_bf16(-st0.x, -st0.x), q ? 0u : pack_bf16(-st1.x, -st1.x), 0u, 0u, desc_sbo(desc_lo_b(sb + OVF, 256), 0), 1);
        wgmma_commit();
        if (wg) asm volatile("bar.arrive 5, 256;" ::: "memory");
        const uint32_t ep1 = lds_u32(sb + S_EP), role = lds_u32(sb + S_ROLE);
        const bool first = (warp & 5) == 0 && role < 4;
        const bool e0 = 2 * q > g, e1 = 2 * q + 1 > g;
        float fs[2][2], fp[2][2], fb[2];
        {
          const uint4 kk = lds_u4(sb + TAB + (warp * 16 + 2 * q) * 8);
          const float c = 0.23570226039551584f * 1.4426950408889634f;
          fp[0][0] = e0 ? 1.f : __uint_as_float(kk.y);
          fp[0][1] = e1 ? 1.f : __uint_as_float(kk.w);
          fp[1][0] = e0 ? __uint_as_float(kk.y) : 1.f;
          fp[1][1] = e1 ? __uint_as_float(kk.w) : 1.f;
#pragma unroll
          for (int i = 0; i < 4; ++i) fs[i >> 1][i & 1] = fp[i >> 1][i & 1] * ((i >> 1) ? st1.y : st0.y) * c;
          fb[0] = first && e0 ? -INFINITY : 0.f;
          fb[1] = first && e1 ? -INFINITY : 0.f;
        }
        wgmma_wait<0>();
        release_slot(sb, 4);
        if (lane == 0) {
          if (!(warp & 3)) mbar_expect_tx(sb + B_OX + 8 * wg, 10240);
          mbar_arrive_cluster(mapa(sb + B_RX + 8 * wg, rank ^ 1));
        }
        TS(1);
        uint32_t X[3][9][2], PK[9], PV[9];
#pragma unroll
        for (int pp = 0; pp < 3; ++pp) {
          const int part = (pp + 1) % 3;
          auto pack = [&](auto R) {
#pragma unroll
            for (int i = 0; i < 9; ++i) {
              const int c = (i + 9 - decltype(R)::value) % 9, jj = c < 8 ? part * 8 + c : 24 + part;
              X[part][i][0] = pack_bf16(acc[4 * jj], acc[4 * jj + 1]);
              X[part][i][1] = part ? pack_bf16(acc[4 * jj + 2] * st1.y, acc[4 * jj + 3] * st1.y) : pack_bf16(acc[4 * jj + 2], acc[4 * jj + 3]);
            }
          };
          if (rank) pack(IC<1>{});
          else pack(IC<0>{});
          if (part == 2) {
#pragma unroll
            for (int i = 0; i < 9; ++i) X[2][i][1] = movm(X[2][i][1]);
          }
          if (pp == 1) {
            const int sw = (warp & 1) ? warp + 3 : warp + 1;
            if (sw >= 8) {
              uint4* hp = g_halo + (role * 2 + rank) * 384 + (warp & 2) * 96 + lane;
#pragma unroll
              for (int i = 0; i < 6; ++i) {
                const int c = 3 * (i % 3);
                st_tagged(hp + i * 32, X[1 + i / 3][c][1], X[1 + i / 3][c + 1][1], X[1 + i / 3][c + 2][1], 2 * ep1 + L);
              }
            } else {
              const uint32_t ad = sb + (sw >> 2) * HALF + TILE + (sw & 3) * 2048 + lane * 16;
#pragma unroll
              for (int i = 0; i < 6; ++i) {
                const int c = 3 * (i % 3);
                sts_u4(ad + (i >> 2) * TILE + (i & 3) * 512, X[1 + i / 3][c][1], X[1 + i / 3][c + 1][1], X[1 + i / 3][c + 2][1],
                       X[1 + i / 3][c + 2][1]);
              }
              __syncwarp();
              if (lane == 0) mbar_arrive(sb + B_NB + 8 * sw);
            }
#pragma unroll
            for (int i = 0; i < 9; ++i) X[2][i][0] = movm(X[2][i][0]);
          }
        }
        uint32_t qf[4][2], ql[4][2];
        float sc[4][3][4];
#pragma unroll
        for (int h = 0; h < 4; ++h) {
#pragma unroll
          for (int r = 0; r < 2; ++r) {
            qf[h][r] = q >= h ? X[0][2 * h][r] : 0u;
            ql[h][r] = q <= h ? X[0][2 * h + 2][r] : 0u;
          }
#pragma unroll
          for (int t = 1; t < 3; ++t) {
            mma_1688(sc[h][t], ql[h][0], ql[h][1], X[1][2 * h + 2][t - 1]);
            mma_16816(sc[h][t], qf[h][0], qf[h][1], X[0][2 * h + 1][0], X[0][2 * h + 1][1], X[1][2 * h][t - 1], X[1][2 * h + 1][t - 1]);
          }
        }
        mbar_wait(sb + B_NB + 8 * warp, L);
#pragma unroll
        for (int i = 0; i < 6; ++i) {
          const uint4 u = lds_u4(sb + wg * HALF + TILE + (warp & 3) * 2048 + lane * 16 + (i >> 2) * TILE + (i & 3) * 512);
          uint32_t(&d)[9] = i < 3 ? PK : PV;
          d[3 * (i % 3)] = u.x;
          d[3 * (i % 3) + 1] = u.y;
          d[3 * (i % 3) + 2] = u.z;
        }
        TS(3);
#pragma unroll
        for (int h = 0; h < 4; ++h) {
          mma_1688(sc[h][0], ql[h][0], ql[h][1], PK[2 * h + 2]);
          mma_16816(sc[h][0], qf[h][0], qf[h][1], X[0][2 * h + 1][0], X[0][2 * h + 1][1], PK[2 * h], PK[2 * h + 1]);
        }
        float pr[4][2][2], mx[4][2];
#pragma unroll
        for (int h = 0; h < 4; ++h)
#pragma unroll
          for (int r = 0; r < 2; ++r) {
            pr[h][r][0] = fmaf(e0 ? sc[h][r][2 * r] : sc[h][r + 1][2 * r], fs[r][0], r ? 0.f : fb[0]);
            pr[h][r][1] = fmaf(e1 ? sc[h][r][2 * r + 1] : sc[h][r + 1][2 * r + 1], fs[r][1], r ? 0.f : fb[1]);
            mx[h][r] = fmaxf(pr[h][r][0], pr[h][r][1]);
          }
#pragma unroll
        for (int o = 1; o <= 2; ++o)
#pragma unroll
          for (int i = 0; i < 8; ++i) mx[i >> 1][i & 1] = fmaxf(mx[i >> 1][i & 1], __shfl_xor_sync(0xffffffffu, mx[i >> 1][i & 1], o));
#pragma unroll
        for (int h = 0; h < 4; ++h)
#pragma unroll
          for (int r = 0; r < 2; ++r) {
#pragma unroll
            for (int e = 0; e < 2; ++e) asm("ex2.approx.ftz.f32 %0, %1;" : "=f"(pr[h][r][e]) : "f"(pr[h][r][e] - mx[h][r]));
            mx[h][r] = pr[h][r][0] + pr[h][r][1];
            pr[h][r][0] *= fp[r][0];
            pr[h][r][1] *= fp[r][1];
          }
#pragma unroll
        for (int o = 1; o <= 2; ++o)
#pragma unroll
          for (int i = 0; i < 8; ++i) mx[i >> 1][i & 1] += __shfl_xor_sync(0xffffffffu, mx[i >> 1][i & 1], o);
        const uint32_t me = (e0 ? 0xFFFFu : 0u) | (e1 ? 0xFFFF0000u : 0u);
        float oc[4][3][4];
#pragma unroll
        for (int h = 0; h < 4; ++h) {
          uint32_t pp[2];
#pragma unroll
          for (int r = 0; r < 2; ++r) {
            float inv;
            asm("rcp.approx.ftz.f32 %0, %1;" : "=f"(inv) : "f"(mx[h][r]));
            pp[r] = pack_bf16(pr[h][r][0] * inv, pr[h][r][1] * inv);
          }
#pragma unroll
          for (int c = 0; c < 3; ++c) {
            mma_1688(oc[h][c], 0u, pp[1] & ~me, X[2][2 * h + c][1]);
            mma_16816(oc[h][c], pp[0] & me, 0u, pp[0] & ~me, pp[1] & me, PV[2 * h + c], X[2][2 * h + c][0]);
          }
        }
        float2 ws[9];
#pragma unroll
        for (int i = 0; i < 9; ++i) ws[i] = lds_f2(sb + S_WS + i * 32 + 8 * q);
        uint32_t of[9][2];
#pragma unroll
        for (int i = 0; i < 9; ++i) {
          const int h = i < 8 ? i >> 1 : 3;
          float(&o)[4] = oc[h][i - 2 * h];
          if (i == 2 || i == 4 || i == 6) {
#pragma unroll
            for (int e = 0; e < 4; ++e) o[e] = q < h ? oc[h - 1][2][e] : o[e];
          }
          of[i][0] = pack_bf16(o[0], o[1]);
          of[i][1] = pack_bf16(o[2], o[3]);
        }
        TS(5);
        float wa[3][32];
        const uint32_t dw0 = desc_lo_b(sb + RING, 0);
        mbar_wait(sb + B_FULL, L ^ 1);
        wgmma_fence();
#pragma unroll
        for (int k = 0; k < 5; ++k)
          wgmma_rs<64>(wa[0], of[2 * k][0], of[2 * k][1], k < 4 ? of[2 * k + 1][0] : 0u, k < 4 ? of[2 * k + 1][1] : 0u,
                       desc_sbo(dw0 + k * 128, k < 4 ? 1024 : 0), k);
        wgmma_commit();
        const uint32_t xa = sb + wg * HALF + 3 * TILE + (warp & 3) * 2048 + lane * 16;
        const uint32_t xr = mapa(xa + (rank ^ 1) * TILE, rank ^ 1), xb = mapa(sb + B_OX + 8 * wg, rank ^ 1);
        mbar_wait(sb + B_RX + 8 * wg, L);
#pragma unroll
        for (int i = 0; i < 4; ++i) st_async_u4(xr + i * 512, xb, of[2 * i][0], of[2 * i][1], of[2 * i + 1][0], of[2 * i + 1][1]);
        float sh0 = 0.f, sh1 = 0.f;
#pragma unroll
        for (int i = 0; i < 9; ++i) {
          const int h = i < 8 ? i >> 1 : 3;
          sh0 = fmaf(oc[h][i - 2 * h][0], ws[i].x, fmaf(oc[h][i - 2 * h][1], ws[i].y, sh0));
          sh1 = fmaf(oc[h][i - 2 * h][2], ws[i].x, fmaf(oc[h][i - 2 * h][3], ws[i].y, sh1));
        }
        sh0 = fmaf(quad_sum(sh0), 1.0f / DM, st0.x * 0.125f);
        sh1 = fmaf(quad_sum(sh1), 1.0f / DM, st1.x * 0.125f);
        st_async_u4(xr + 2 * TILE, xb, of[8][0], of[8][1], __float_as_uint(sh0), __float_as_uint(sh1));
        wgmma_wait<0>();
        stage_tile(wa[0], 1.f, -sh0, 1.f, -sh1, sb, 0, 0, 1);
        TS(6);
        if (q < 2) sts_u32(sb + TAB + (warp * 16 + g + 8 * q) * 8, __float_as_uint(q ? sh1 : sh0));
        mbar_wait(sb + B_OX + 8 * wg, L);
        uint4 xv[5];
#pragma unroll
        for (int i = 0; i < 5; ++i) xv[i] = lds_u4(xa + rank * TILE + (i < 4 ? i * 512 : 2 * TILE));
        sh0 += __uint_as_float(xv[4].z);
        sh1 += __uint_as_float(xv[4].w);
        TS(4);
        auto issue = [&](auto I) {
          constexpr int i = decltype(I)::value;
          mbar_wait(sb + B_FULL + 8 * i, (i == 1) ^ L);
          const uint32_t lo = dw0 + (2 * i - 1) * (WOA / 16);
          wgmma_fence();
#pragma unroll
          for (int k = 0; k < 4; ++k)
            wgmma_rs<64>(wa[i % 3], of[2 * k][0], of[2 * k][1], of[2 * k + 1][0], of[2 * k + 1][1], desc_sbo(lo + k * 128, 1024), k);
          wgmma_rs<64>(wa[i % 3], of[8][0], of[8][1], xv[4].x, xv[4].y, desc_sbo(lo + 512, WOA), 1);
#pragma unroll
          for (int k = 0; k < 4; ++k)
            wgmma_rs<64>(wa[i % 3], xv[k].x, xv[k].y, xv[k].z, xv[k].w, desc_sbo(lo + WOA / 16 + k * 128, 1024), 1);
          wgmma_commit();
        };
        issue(IC<1>{});
        issue(IC<2>{});
        wgmma_wait<1>();
        release_slot(sb, 0);
        stage_tile(wa[1], 1.f, -sh0, 1.f, -sh1, sb, 1 + rank, 1, 1);
        issue(IC<3>{});
        issue(IC<4>{});
        wgmma_wait<2>();
        release_slot(sb, 1);
        stage_tile(wa[2], 1.f, -sh0, 1.f, -sh1, sb, 3 + rank, 0, 0);
        wgmma_wait<1>();
        release_slot(sb, 2);
        stage_tile(wa[0], 1.f, -sh0, 1.f, -sh1, sb, 5 + rank, 0, 0);
        wgmma_wait<0>();
        release_slot(sb, 3);
        release_slot(sb, 4);
        stage_tile(wa[1], 1.f, -sh0, 1.f, -sh1, sb, 7 + rank, 2, 7);
        TS(7);
      }
      uint32_t hreg[9][16];
      {
        const int wg = warp >> 2;
        float acc[64];
        int p = 0;
        uint32_t ph = L;
        const uint32_t da0 = desc_lo_a(sb + wg * HALF), db0 = desc_lo_b(sb + RING, 8192);
        float prod[32];
        {
          float acc0[64], acc1[64], acc2[64];
#pragma unroll
          for (int i = 0; i < 64; ++i) acc0[i] = acc1[i] = acc2[i] = 0.f;
          auto step = [&](float(&d)[64], int kb, bool rel) {
            mbar_wait(sb + B_FULL + 8 * p, ph);
            wgmma_fence();
#pragma unroll
            for (int k = 0; k < 4; ++k)
              wgmma_ss<128>(d, desc_from_lo(da0 + kb * 512 + k * 2), desc_from_lo(db0 + p * 1024 + k * 128), 1);
            wgmma_commit();
            wgmma_wait<1>();
            release_slot(sb, p == 0 ? 4 : p - 1, rel);
            if (++p == 5) p = 0;
            if (p == 2) ph ^= 1;
          };
#pragma unroll 1
          for (int kb = 0; kb < 9; ++kb) {
            mbar_wait(sb + B_FX + 72 * wg + 8 * kb, 1);
            if (kb == 0) TS(9);
            TR(16 + kb);
            step(acc0, kb, kb > 0);
            step(acc1, kb, true);
            step(acc2, kb, true);
          }
#pragma unroll
          for (int i = 0; i < 16; ++i) {
            hreg[0][i] = pack_bf16(acc0[2 * i] * acc0[32 + 2 * i], acc0[2 * i + 1] * acc0[33 + 2 * i]);
            hreg[1][i] = pack_bf16(acc1[2 * i] * acc1[32 + 2 * i], acc1[2 * i + 1] * acc1[33 + 2 * i]);
          }
          mbar_wait(sb + B_FULL + 8 * p, ph);
          wgmma_wait<0>();
#pragma unroll
          for (int i = 0; i < 32; ++i) prod[i] = acc2[i] * acc2[32 + i];
        }
#pragma unroll
        for (int t = 2; t < 8; ++t)
#pragma unroll
          for (int i = 0; i < 16; ++i) hreg[t][i] = 0u;
        TS(10);
#pragma unroll 1
        for (int t = 3; t < 9; ++t) {
          wgmma_fence();
#pragma unroll
          for (int k = 0; k < 4; ++k)
            wgmma_ss<128>(acc, desc_from_lo(da0 + k * 2), desc_from_lo(db0 + p * 1024 + k * 128), k != 0);
          wgmma_commit();
          release_slot(sb, p == 0 ? 4 : p - 1);
#pragma unroll
          for (int i = 0; i < 32; ++i) asm volatile("" : "+f"(prod[i]));
#pragma unroll
          for (int i = 0; i < 16; ++i) hreg[8][i] = pack_bf16(prod[2 * i], prod[2 * i + 1]);
          if (++p == 5) p = 0;
          if (p == 2) ph ^= 1;
#pragma unroll 1
          for (int kb = 1; kb < 9; ++kb) {
            mbar_wait(sb + B_FULL + 8 * p, ph);
            wgmma_fence();
#pragma unroll
            for (int k = 0; k < 4; ++k)
              wgmma_ss<128>(acc, desc_from_lo(da0 + kb * 512 + k * 2), desc_from_lo(db0 + p * 1024 + k * 128), 1);
            wgmma_commit();
            if (kb == 1) {
#pragma unroll
              for (int tt = 2; tt < 8; ++tt)
                if (t == tt + 1) {
#pragma unroll
                  for (int i = 0; i < 16; ++i) asm volatile("mov.b32 %0, %1;" : "=r"(hreg[tt][i]) : "r"(hreg[8][i]));
                }
            }
            wgmma_wait<1>();
            release_slot(sb, p == 0 ? 4 : p - 1);
            if (++p == 5) p = 0;
            if (p == 2) ph ^= 1;
          }
          mbar_wait(sb + B_FULL + 8 * p, ph);
          wgmma_wait<0>();
#pragma unroll
          for (int i = 0; i < 32; ++i) prod[i] = acc[i] * acc[32 + i];
          TR(32 + t);
        }
#pragma unroll
        for (int i = 0; i < 16; ++i) hreg[8][i] = pack_bf16(prod[2 * i], prod[2 * i + 1]);
      }
      TS(11);
      {
        float accA[32], accB[32];
        int p = 1;
        uint32_t ph = L;
        const uint32_t db0 = desc_lo_b(sb + RING, 8192);
        int prev = 0, left = 35;
        auto stage = [&](auto S, auto NU, bool rel) {
          constexpr int s = decltype(S)::value;
          mbar_wait(sb + B_FULL + 8 * p, ph ^ (p >= 5));
          const uint32_t dlo = p < 5 ? db0 + p * 1024 : db0 - RING / 16 + 1024 + p * 512, dv = p < 5 ? 512 : HALF / 16;
          wgmma_fence();
#pragma unroll
          for (int v = 0; v < decltype(NU)::value; ++v) {
            const int u = 2 * s + v, kq = u % 9;
#pragma unroll
            for (int k = 0; k < 4; ++k)
              wgmma_rs<64>(u >= 9 ? accB : accA, hreg[kq][4 * k], hreg[kq][4 * k + 1], hreg[kq][4 * k + 2], hreg[kq][4 * k + 3],
                           desc_from_lo(dlo + v * dv + k * 128), (kq | k) != 0);
          }
          wgmma_commit();
          if (rel) {
            wgmma_wait<1>();
            release_slot(sb, prev, prev < 5 || left > 2);
          }
          prev = p;
          --left;
          if (++p == (left > 0 ? 7 : 5)) p = 0;
          if (p == 2) ph ^= 1;
        };
        stage(IC<0>{}, IC<2>{}, false);
        release_slot(sb, 0);
        mbar_wait(sb + B_SR, 1);
        release_slot(sb, 5);
        release_slot(sb, 6);
        const uint32_t ta = sb + TAB + warp * 128 + (tid_now() & 28) * 2;
        const float2 t0 = lds_f2(ta), t1 = lds_f2(ta + 64);
        const float m0 = t0.y, c0 = t0.x, m1 = t1.y, c1 = t1.x;
#pragma unroll 1
        for (int i = 0; i < 4; ++i) {
          stage(IC<1>{}, IC<2>{}, true);
          stage(IC<2>{}, IC<2>{}, true);
          stage(IC<3>{}, IC<2>{}, true);
          stage(IC<4>{}, IC<2>{}, true);
          stage(IC<5>{}, IC<2>{}, true);
          stage_tile(accA, m0, c0, m1, c1, sb, 2 * i, 2 * i, 1);
          TR(48 + 2 * i);
          stage(IC<6>{}, IC<2>{}, true);
          stage(IC<7>{}, IC<2>{}, true);
          if (i == 3 && (tid_now() & 31) == 0) mbar_arrive(sb + B_XF);
          stage(IC<8>{}, IC<2>{}, true);
          stage(IC<0>{}, IC<2>{}, true);
          if (i == 3) mbar_wait(sb + B_XF, L);
          stage_tile(accB, m0, c0, m1, c1, sb, 2 * i + 1, 2 * i + 1, 1);
          TR(49 + 2 * i);
        }
        stage(IC<1>{}, IC<2>{}, true);
        stage(IC<2>{}, IC<2>{}, true);
        stage(IC<3>{}, IC<2>{}, true);
        stage(IC<4>{}, IC<1>{}, true);
        wgmma_wait<0>();
        release_slot(sb, 1);
        stage_tile(accA, m0, c0, m1, c1, sb, 8, 8, 1);
        TR(56);
        TS(12);
      }
    }
  }
}

__global__ void probe_kernel() {}

typedef CUresult (*PFN_tmEncode)(CUtensorMap*, CUtensorMapDataType, cuuint32_t, void*, const cuuint64_t*,
                                 const cuuint64_t*, const cuuint32_t*, const cuuint32_t*, CUtensorMapInterleave,
                                 CUtensorMapSwizzle, CUtensorMapL2promotion, CUtensorMapFloatOOBfill);

static void encode_2d(PFN_tmEncode fn, CUtensorMap* m, const void* ptr, uint64_t inner, uint64_t outer, uint32_t box_inner,
                      uint32_t box_outer) {
  cuuint64_t dims[2] = {inner, outer};
  cuuint64_t strides[1] = {inner * 2};
  cuuint32_t box[2] = {box_inner, box_outer};
  cuuint32_t estr[2] = {1, 1};
  fn(m, CU_TENSOR_MAP_DATA_TYPE_BFLOAT16, 2, const_cast<void*>(ptr), dims, strides, box, estr,
     CU_TENSOR_MAP_INTERLEAVE_NONE, CU_TENSOR_MAP_SWIZZLE_128B, CU_TENSOR_MAP_L2_PROMOTION_L2_256B,
     CU_TENSOR_MAP_FLOAT_OOB_FILL_NONE);
}

static void encode_3d(PFN_tmEncode fn, CUtensorMap* m, const void* ptr, uint64_t d0, uint64_t d1, uint64_t d2, uint64_t s1,
                      uint64_t s2, uint32_t b0, uint32_t b1, uint32_t b2, CUtensorMapL2promotion prom) {
  cuuint64_t dims[3] = {d0, d1, d2};
  cuuint64_t strides[2] = {s1, s2};
  cuuint32_t box[3] = {b0, b1, b2};
  cuuint32_t estr[3] = {1, 1, 1};
  fn(m, CU_TENSOR_MAP_DATA_TYPE_BFLOAT16, 3, const_cast<void*>(ptr), dims, strides, box, estr, CU_TENSOR_MAP_INTERLEAVE_NONE,
     CU_TENSOR_MAP_SWIZZLE_128B, prom, CU_TENSOR_MAP_FLOAT_OOB_FILL_NONE);
}

}

extern "C" void kernel_launch(void* const* d_in, const int* in_sizes, int n_in, void* d_out, int out_size) {
  const __nv_bfloat16* x0 = (const __nv_bfloat16*)d_in[0];
  const __nv_bfloat16* wqkv = (const __nv_bfloat16*)d_in[1];
  const __nv_bfloat16* wo = (const __nv_bfloat16*)d_in[2];
  const __nv_bfloat16* wg = (const __nv_bfloat16*)d_in[4];
  const __nv_bfloat16* wu = (const __nv_bfloat16*)d_in[5];
  const __nv_bfloat16* wd = (const __nv_bfloat16*)d_in[6];
  static PFN_tmEncode enc = nullptr;
  if (!enc) {
    void* fn = nullptr;
    cudaDriverEntryPointQueryResult qr;
    cudaGetDriverEntryPoint("cuTensorMapEncodeTiled", &fn, cudaEnableDefault, &qr);
    enc = (PFN_tmEncode)fn;
  }
  Maps mp;
  encode_3d(enc, &mp.x0, x0, DM, SEQ / 2, 2, DM * 4, DM * 2, 64, 32, 2, CU_TENSOR_MAP_L2_PROMOTION_L2_256B);
  encode_3d(enc, &mp.r, d_out, DM, SEQ / 2, 2, DM * 4, DM * 2, 64, 32, 2, CU_TENSOR_MAP_L2_PROMOTION_L2_256B);
  encode_3d(enc, &mp.wq, wqkv, 576, 576, 3, NQKV * 2, 576 * 2, 64, 16, 3, CU_TENSOR_MAP_L2_PROMOTION_L2_128B);
  encode_2d(enc, &mp.wo, wo, DM, DM, 64, 72);
  encode_2d(enc, &mp.wg, wg, FF, DM, 64, 64);
  encode_2d(enc, &mp.wu, wu, FF, DM, 64, 64);
  encode_2d(enc, &mp.wd, wd, DM, FF, 64, 64);
  cudaFuncSetAttribute(mega_kernel, cudaFuncAttributeMaxDynamicSharedMemorySize, SMEM_BYTES);
  static int small_gpc = -1;
  if (small_gpc < 0) {
    cudaFuncSetAttribute(probe_kernel, cudaFuncAttributeMaxDynamicSharedMemorySize, SMEM_BYTES);
    cudaFuncSetAttribute(probe_kernel, cudaFuncAttributeNonPortableClusterSizeAllowed, 1);
    int n[2] = {0, 0};
    for (int i = 0; i < 2; ++i) {
      cudaLaunchConfig_t cfg = {};
      cfg.gridDim = dim3(128);
      cfg.blockDim = dim3(384);
      cfg.dynamicSmemBytes = SMEM_BYTES;
      cudaLaunchAttribute at;
      at.id = cudaLaunchAttributeClusterDimension;
      at.val.clusterDim.x = 8 << i;
      at.val.clusterDim.y = at.val.clusterDim.z = 1;
      cfg.attrs = &at;
      cfg.numAttrs = 1;
      if (cudaOccupancyMaxActiveClusters(&n[i], probe_kernel, &cfg) != cudaSuccess) cudaGetLastError();
    }
    small_gpc = n[0] == 15 && n[1] == 7;
  }
  mega_kernel<<<128, 384, SMEM_BYTES, cudaStreamPerThread>>>(mp, x0, wqkv, wo, (__nv_bfloat16*)d_out, small_gpc);
}
```

```cpp
#include <cuda_runtime.h>
#include <cuda_bf16.h>
#include <cuda.h>
#include <stdint.h>

namespace {

constexpr int SEQ = 2048, DM = 576, FF = 4608, NQKV = 1728;

__device__ __align__(128) uint4 g_halo[128 * 384];
__device__ __align__(128) uint4 g_stat[SEQ];
__device__ __align__(128) float g_csq[4 * NQKV];
__device__ __align__(128) float g_wsum[DM];
constexpr int FL_J = 64 * 32;
__device__ __align__(128) unsigned int g_flag[FL_J + 32];
__device__ unsigned int g_epoch[128];
__device__ unsigned int g_claim[8];

__device__ __forceinline__ uint32_t smem_u32(const void* p) { return (uint32_t)__cvta_generic_to_shared(p); }
__device__ __forceinline__ void mbar_init(uint32_t bar, uint32_t count) {
  asm volatile("mbarrier.init.shared::cta.b64 [%0], %1;" ::"r"(bar), "r"(count) : "memory");
}
__device__ __forceinline__ void mbar_expect_tx(uint32_t bar, uint32_t bytes) {
  asm volatile("mbarrier.arrive.expect_tx.shared::cta.b64 _, [%0], %1;" ::"r"(bar), "r"(bytes) : "memory");
}
__device__ __forceinline__ void mbar_arrive(uint32_t bar) {
  asm volatile("mbarrier.arrive.shared::cta.b64 _, [%0];" ::"r"(bar) : "memory");
}
#define SPIN_LIMIT "1048576"
#define SPIN_MAX 1048576
__device__ __forceinline__ void mbar_wait(uint32_t bar, uint32_t parity) {
  asm volatile(
      "{\n.reg .pred p, c;\n.reg .u32 n;\nmov.u32 n, 0;\n"
      "WAIT:\nmbarrier.try_wait.parity.shared::cta.b64 p, [%0], %1;\n"
      "add.u32 n, n, 1;\nsetp.lt.and.u32 c, n, " SPIN_LIMIT ", !p;\n@c bra.uni WAIT;\n}"
      :
      : "r"(bar), "r"(parity)
      : "memory");
}
__device__ __forceinline__ bool mbar_test(uint32_t bar, uint32_t parity) {
  uint32_t r;
  asm volatile("{\n.reg .pred p;\nmbarrier.try_wait.parity.shared::cta.b64 p, [%1], %2;\nselp.u32 %0, 1, 0, p;\n}"
               : "=r"(r) : "r"(bar), "r"(parity) : "memory");
  return r != 0;
}
__device__ __forceinline__ void poll_ge(const unsigned int* p, unsigned int target) {
  asm volatile(
      "{\n.reg .pred p, c;\n.reg .u32 n;\n.reg .s32 v;\nmov.u32 n, 0;\n"
      "POLL:\nld.relaxed.gpu.global.u32 v, [%0];\nsub.s32 v, v, %1;\nsetp.lt.s32 p, v, 0;\n"
      "add.u32 n, n, 1;\nsetp.lt.and.u32 c, n, " SPIN_LIMIT ", p;\n@c bra.uni POLL;\n}"
      :
      : "l"(p), "r"(target)
      : "memory");
}
__device__ __forceinline__ void signal_release(unsigned int* p, uint32_t v = 1) {
  asm volatile("red.release.gpu.global.add.u32 [%0], %1;" ::"l"(p), "r"(v) : "memory");
}
__device__ __forceinline__ void signal_relaxed(unsigned int* p, uint32_t v = 1) {
  asm volatile("red.relaxed.gpu.global.add.u32 [%0], %1;" ::"l"(p), "r"(v) : "memory");
}
__device__ __forceinline__ bool elect_one() {
  uint32_t pred;
  asm volatile("{\n.reg .pred p;\nelect.sync _|p, 0xffffffff;\nselp.u32 %0, 1, 0, p;\n}" : "=r"(pred));
  return pred != 0;
}
__device__ __forceinline__ void tma_load_2d(uint32_t dst, const CUtensorMap* map, uint32_t bar, int c0, int c1) {
  asm volatile(
      "cp.async.bulk.tensor.2d.shared::cluster.global.mbarrier::complete_tx::bytes [%0], [%1, {%3, %4}], [%2];" ::"r"(dst),
      "l"(map), "r"(bar), "r"(c0), "r"(c1)
      : "memory");
}
__device__ __forceinline__ void tma_load_3d(uint32_t dst, const CUtensorMap* map, uint32_t bar, int c0, int c1, int c2) {
  asm volatile(
      "cp.async.bulk.tensor.3d.shared::cluster.global.mbarrier::complete_tx::bytes [%0], [%1, {%3, %4, %5}], [%2];" ::"r"(dst),
      "l"(map), "r"(bar), "r"(c0), "r"(c1), "r"(c2)
      : "memory");
}
__device__ __forceinline__ void tma_load_3d_mc(uint32_t dst, const CUtensorMap* map, uint32_t bar, int c0, int c1, int c2) {
  asm volatile(
      "cp.async.bulk.tensor.3d.shared::cluster.global.mbarrier::complete_tx::bytes.multicast::cluster [%0], [%1, {%3, "
      "%4, %5}], [%2], %6;" ::"r"(dst),
      "l"(map), "r"(bar), "r"(c0), "r"(c1), "r"(c2), "h"((uint16_t)3)
      : "memory");
}
__device__ __forceinline__ void st_async_u4(uint32_t dst, uint32_t bar, uint32_t a, uint32_t b, uint32_t c, uint32_t d) {
  asm volatile("st.async.weak.shared::cluster.mbarrier::complete_tx::bytes.v4.b32 [%0], {%2, %3, %4, %5}, [%1];" ::"r"(dst),
               "r"(bar), "r"(a), "r"(b), "r"(c), "r"(d)
               : "memory");
}
__device__ __forceinline__ void mbar_arrive_cluster(uint32_t bar_cluster_addr) {
  asm volatile("mbarrier.arrive.shared::cluster.b64 _, [%0];" ::"r"(bar_cluster_addr) : "memory");
}
__device__ __forceinline__ void tma_reduce_3d(const CUtensorMap* map, uint32_t src, int c0, int c1, int c2) {
  asm volatile("cp.reduce.async.bulk.tensor.3d.global.shared::cta.add.tile.bulk_group [%0, {%2, %3, %4}], [%1];" ::"l"(map),
               "r"(src), "r"(c0), "r"(c1), "r"(c2)
               : "memory");
}
__device__ __forceinline__ void tma_store_3d(const CUtensorMap* map, uint32_t src, int c0, int c1, int c2) {
  asm volatile("cp.async.bulk.tensor.3d.global.shared::cta.tile.bulk_group [%0, {%2, %3, %4}], [%1];" ::"l"(map), "r"(src),
               "r"(c0), "r"(c1), "r"(c2)
               : "memory");
}
__device__ __forceinline__ void tma_prefetch_2d(const CUtensorMap* map, int c0, int c1) {
  asm volatile("cp.async.bulk.prefetch.tensor.2d.L2.global.tile [%0, {%1, %2}];" ::"l"(map), "r"(c0), "r"(c1) : "memory");
}
__device__ __forceinline__ void prefetch_map(const CUtensorMap* map) {
  asm volatile("prefetch.tensormap [%0];" ::"l"(map) : "memory");
}
__device__ __forceinline__ void wgmma_fence() { asm volatile("wgmma.fence.sync.aligned;" ::: "memory"); }
__device__ __forceinline__ void wgmma_commit() { asm volatile("wgmma.commit_group.sync.aligned;" ::: "memory"); }
template <int N>
__device__ __forceinline__ void wgmma_wait() {
  asm volatile("wgmma.wait_group.sync.aligned %0;" ::"n"(N) : "memory");
}
__device__ __forceinline__ void named_bar_sync(int id, int nthreads) {
  asm volatile("bar.sync %0, %1;" ::"r"(id), "r"(nthreads) : "memory");
}
__device__ __forceinline__ void cluster_arrive_relaxed() { asm volatile("barrier.cluster.arrive.relaxed.aligned;" ::: "memory"); }
__device__ __forceinline__ void cluster_wait() { asm volatile("barrier.cluster.wait.acquire.aligned;" ::: "memory"); }
__device__ __forceinline__ uint32_t mapa(uint32_t addr, uint32_t rank) {
  uint32_t r;
  asm volatile("mapa.shared::cluster.u32 %0, %1, %2;" : "=r"(r) : "r"(addr), "r"(rank));
  return r;
}
__device__ __forceinline__ uint64_t desc_from_lo(uint32_t lo) { return (uint64_t)lo | (0x40000040ull << 32); }
__device__ __forceinline__ uint64_t desc_sbo(uint32_t lo, uint32_t sbo) { return (uint64_t)lo | ((0x40000000ull | (sbo >> 4)) << 32); }
__device__ __forceinline__ uint32_t desc_lo_a(uint32_t addr) { return ((addr & 0x3FFFF) >> 4) | (1u << 16); }
__device__ __forceinline__ uint32_t desc_lo_b(uint32_t addr, uint32_t lbo_bytes) { return ((addr & 0x3FFFF) >> 4) | ((lbo_bytes >> 4) << 16); }
__device__ __forceinline__ uint32_t pack_bf16(float lo, float hi) {
  __nv_bfloat162 v = __floats2bfloat162_rn(lo, hi);
  return *reinterpret_cast<uint32_t*>(&v);
}
__device__ __forceinline__ float bf16r(float x) { return __uint_as_float(pack_bf16(0.f, x)); }
__device__ __forceinline__ float bf_lo(uint32_t u) { return __uint_as_float(u << 16); }
__device__ __forceinline__ float bf_hi(uint32_t u) { return __uint_as_float(u & 0xFFFF0000u); }
__device__ __forceinline__ uint4 lds_u4(uint32_t addr) {
  uint4 v;
  asm volatile("ld.shared.v4.b32 {%0, %1, %2, %3}, [%4];" : "=r"(v.x), "=r"(v.y), "=r"(v.z), "=r"(v.w) : "r"(addr) : "memory");
  return v;
}
__device__ __forceinline__ float2 lds_f2(uint32_t addr) {
  float2 v;
  asm volatile("ld.shared.v2.f32 {%0, %1}, [%2];" : "=f"(v.x), "=f"(v.y) : "r"(addr) : "memory");
  return v;
}
__device__ __forceinline__ void sts_f2(uint32_t addr, float a, float b) {
  asm volatile("st.shared.v2.f32 [%0], {%1, %2};" ::"r"(addr), "f"(a), "f"(b) : "memory");
}
__device__ __forceinline__ void sts_u4(uint32_t addr, uint32_t a, uint32_t b, uint32_t c, uint32_t d) {
  asm volatile("st.shared.v4.b32 [%0], {%1, %2, %3, %4};" ::"r"(addr), "r"(a), "r"(b), "r"(c), "r"(d) : "memory");
}
__device__ __forceinline__ void sts_u32(uint32_t addr, uint32_t v) { asm volatile("st.shared.b32 [%0], %1;" ::"r"(addr), "r"(v) : "memory"); }
__device__ __forceinline__ uint32_t lds_u32(uint32_t addr) {
  uint32_t v;
  asm volatile("ld.shared.b32 %0, [%1];" : "=r"(v) : "r"(addr) : "memory");
  return v;
}
__device__ __forceinline__ uint4 ldg_u4(const void* p, bool on = true) {
  uint4 v = make_uint4(0u, 0u, 0u, 0u);
  asm volatile("{\n.reg .pred p;\nsetp.ne.u32 p, %5, 0;\n@p ld.global.nc.L1::no_allocate.v4.b32 {%0, %1, %2, %3}, [%4];\n}"
               : "+r"(v.x), "+r"(v.y), "+r"(v.z), "+r"(v.w) : "l"(p), "r"((uint32_t)on) : "memory");
  return v;
}
__device__ __forceinline__ float4 ldg_cg_f4(const void* p) {
  float4 v;
  asm volatile("ld.global.cg.v4.f32 {%0, %1, %2, %3}, [%4];" : "=f"(v.x), "=f"(v.y), "=f"(v.z), "=f"(v.w) : "l"(p) : "memory");
  return v;
}
__device__ __forceinline__ void st_tagged(void* p, uint32_t a, uint32_t b, uint32_t c, uint32_t tag) {
  asm volatile("{\n.reg .b64 l, h;\n.reg .b128 v;\nmov.b64 l, {%1, %2};\nmov.b64 h, {%3, %4};\nmov.b128 v, {l, h};\n"
               "st.relaxed.gpu.global.b128 [%0], v;\n}" ::"l"(p), "r"(a), "r"(b), "r"(c), "r"(tag) : "memory");
}
__device__ __forceinline__ uint4 ld_tagged(const void* p) {
  uint4 r;
  asm volatile("{\n.reg .b64 l, h;\n.reg .b128 v;\nld.relaxed.gpu.global.b128 v, [%4];\nmov.b128 {l, h}, v;\n"
               "mov.b64 {%0, %1}, l;\nmov.b64 {%2, %3}, h;\n}" : "=r"(r.x), "=r"(r.y), "=r"(r.z), "=r"(r.w) : "l"(p) : "memory");
  return r;
}
__device__ __forceinline__ void cp_async16(uint32_t dst, const void* src) {
  asm volatile("cp.async.cg.shared.global [%0], [%1], 16;" ::"r"(dst), "l"(src) : "memory");
}
__device__ __forceinline__ void cp_async_arrive(uint32_t bar) {
  asm volatile("cp.async.mbarrier.arrive.shared::cta.b64 [%0];" ::"r"(bar) : "memory");
}
__device__ __forceinline__ void bulk_load(uint32_t dst, const void* gsrc, uint32_t bytes, uint32_t bar) {
  asm volatile("cp.async.bulk.shared::cluster.global.mbarrier::complete_tx::bytes [%0], [%1], %2, [%3];" ::"r"(dst), "l"(gsrc),
               "r"(bytes), "r"(bar)
               : "memory");
}
__device__ __forceinline__ void bulk_commit() { asm volatile("cp.async.bulk.commit_group;" ::: "memory"); }
template <int N>
__device__ __forceinline__ void bulk_wait() { asm volatile("cp.async.bulk.wait_group %0;" ::"n"(N) : "memory"); }
__device__ __forceinline__ void stsm_x4(uint32_t addr, uint32_t a, uint32_t b, uint32_t c, uint32_t d) {
  asm volatile("stmatrix.sync.aligned.m8n8.x4.shared.b16 [%0], {%1, %2, %3, %4};" ::"r"(addr), "r"(a), "r"(b), "r"(c), "r"(d) : "memory");
}
__device__ __forceinline__ uint32_t movm(uint32_t a) {
  uint32_t d;
  asm volatile("movmatrix.sync.aligned.m8n8.trans.b16 %0, %1;" : "=r"(d) : "r"(a));
  return d;
}
__device__ __forceinline__ void mma_16816(float (&d)[4], uint32_t a0, uint32_t a1, uint32_t a2, uint32_t a3, uint32_t b0, uint32_t b1) {
  asm volatile("mma.sync.aligned.m16n8k16.row.col.f32.bf16.bf16.f32 {%0, %1, %2, %3}, {%4, %5, %6, %7}, {%8, %9}, {%0, %1, %2, %3};"
               : "+f"(d[0]), "+f"(d[1]), "+f"(d[2]), "+f"(d[3]) : "r"(a0), "r"(a1), "r"(a2), "r"(a3), "r"(b0), "r"(b1));
}
__device__ __forceinline__ void mma_16816_z(float (&d)[4], uint32_t a0, uint32_t a1, uint32_t a2, uint32_t a3, uint32_t b0, uint32_t b1) {
  asm volatile("mma.sync.aligned.m16n8k16.row.col.f32.bf16.bf16.f32 {%0, %1, %2, %3}, {%4, %5, %6, %7}, {%8, %9}, {%10, %10, %10, %10};"
               : "=f"(d[0]), "=f"(d[1]), "=f"(d[2]), "=f"(d[3]) : "r"(a0), "r"(a1), "r"(a2), "r"(a3), "r"(b0), "r"(b1), "f"(0.f));
}
__device__ __forceinline__ void mma_1688(float (&d)[4], uint32_t a0, uint32_t a1, uint32_t b0) {
  asm volatile("mma.sync.aligned.m16n8k8.row.col.f32.bf16.bf16.f32 {%0, %1, %2, %3}, {%4, %5}, {%6}, {%7, %7, %7, %7};"
               : "=f"(d[0]), "=f"(d[1]), "=f"(d[2]), "=f"(d[3]) : "r"(a0), "r"(a1), "r"(b0), "f"(0.f));
}
__device__ __forceinline__ void fence_proxy_async() { asm volatile("fence.proxy.async.shared::cta;" ::: "memory"); }

template<int N> __device__ __forceinline__ void wgmma_ss(float (&d)[N/2], uint64_t descA, uint64_t descB, int scaleD);
template<int N> __device__ __forceinline__ void wgmma_rs(float (&d)[N/2], uint32_t a0, uint32_t a1, uint32_t a2, uint32_t a3, uint64_t descB, int scaleD);
template<> __device__ __forceinline__ void wgmma_ss<128>(float (&d)[64], uint64_t descA, uint64_t descB, int scaleD) {
  asm volatile("{\n.reg .pred p;\nsetp.ne.b32 p, %66, 0;\n"
    "wgmma.mma_async.sync.aligned.m64n128k16.f32.bf16.bf16 {%0, %1, %2, %3, %4, %5, %6, %7, %8, %9, %10, %11, %12, %13, %14, %15, %16, %17, %18, %19, %20, %21, %22, %23, %24, %25, %26, %27, %28, %29, %30, %31, %32, %33, %34, %35, %36, %37, %38, %39, %40, %41, %42, %43, %44, %45, %46, %47, %48, %49, %50, %51, %52, %53, %54, %55, %56, %57, %58, %59, %60, %61, %62, %63}, %64, %65, p, 1, 1, 0, 1;\n}\n"
    : "+f"(d[0]), "+f"(d[1]), "+f"(d[2]), "+f"(d[3]), "+f"(d[4]), "+f"(d[5]), "+f"(d[6]), "+f"(d[7]), "+f"(d[8]), "+f"(d[9]), "+f"(d[10]), "+f"(d[11]), "+f"(d[12]), "+f"(d[13]), "+f"(d[14]), "+f"(d[15]), "+f"(d[16]), "+f"(d[17]), "+f"(d[18]), "+f"(d[19]), "+f"(d[20]), "+f"(d[21]), "+f"(d[22]), "+f"(d[23]), "+f"(d[24]), "+f"(d[25]), "+f"(d[26]), "+f"(d[27]), "+f"(d[28]), "+f"(d[29]), "+f"(d[30]), "+f"(d[31]), "+f"(d[32]), "+f"(d[33]), "+f"(d[34]), "+f"(d[35]), "+f"(d[36]), "+f"(d[37]), "+f"(d[38]), "+f"(d[39]), "+f"(d[40]), "+f"(d[41]), "+f"(d[42]), "+f"(d[43]), "+f"(d[44]), "+f"(d[45]), "+f"(d[46]), "+f"(d[47]), "+f"(d[48]), "+f"(d[49]), "+f"(d[50]), "+f"(d[51]), "+f"(d[52]), "+f"(d[53]), "+f"(d[54]), "+f"(d[55]), "+f"(d[56]), "+f"(d[57]), "+f"(d[58]), "+f"(d[59]), "+f"(d[60]), "+f"(d[61]), "+f"(d[62]), "+f"(d[63])
    : "l"(descA), "l"(descB), "r"(scaleD));
}
template<> __device__ __forceinline__ void wgmma_ss<216>(float (&d)[108], uint64_t descA, uint64_t descB, int scaleD) {
  asm volatile("{\n.reg .pred p;\nsetp.ne.b32 p, %110, 0;\n"
    "wgmma.mma_async.sync.aligned.m64n216k16.f32.bf16.bf16 {%0, %1, %2, %3, %4, %5, %6, %7, %8, %9, %10, %11, %12, %13, %14, %15, %16, %17, %18, %19, %20, %21, %22, %23, %24, %25, %26, %27, %28, %29, %30, %31, %32, %33, %34, %35, %36, %37, %38, %39, %40, %41, %42, %43, %44, %45, %46, %47, %48, %49, %50, %51, %52, %53, %54, %55, %56, %57, %58, %59, %60, %61, %62, %63, %64, %65, %66, %67, %68, %69, %70, %71, %72, %73, %74, %75, %76, %77, %78, %79, %80, %81, %82, %83, %84, %85, %86, %87, %88, %89, %90, %91, %92, %93, %94, %95, %96, %97, %98, %99, %100, %101, %102, %103, %104, %105, %106, %107}, %108, %109, p, 1, 1, 0, 1;\n}\n"
    : "+f"(d[0]), "+f"(d[1]), "+f"(d[2]), "+f"(d[3]), "+f"(d[4]), "+f"(d[5]), "+f"(d[6]), "+f"(d[7]), "+f"(d[8]), "+f"(d[9]), "+f"(d[10]), "+f"(d[11]), "+f"(d[12]), "+f"(d[13]), "+f"(d[14]), "+f"(d[15]), "+f"(d[16]), "+f"(d[17]), "+f"(d[18]), "+f"(d[19]), "+f"(d[20]), "+f"(d[21]), "+f"(d[22]), "+f"(d[23]), "+f"(d[24]), "+f"(d[25]), "+f"(d[26]), "+f"(d[27]), "+f"(d[28]), "+f"(d[29]), "+f"(d[30]), "+f"(d[31]), "+f"(d[32]), "+f"(d[33]), "+f"(d[34]), "+f"(d[35]), "+f"(d[36]), "+f"(d[37]), "+f"(d[38]), "+f"(d[39]), "+f"(d[40]), "+f"(d[41]), "+f"(d[42]), "+f"(d[43]), "+f"(d[44]), "+f"(d[45]), "+f"(d[46]), "+f"(d[47]), "+f"(d[48]), "+f"(d[49]), "+f"(d[50]), "+f"(d[51]), "+f"(d[52]), "+f"(d[53]), "+f"(d[54]), "+f"(d[55]), "+f"(d[56]), "+f"(d[57]), "+f"(d[58]), "+f"(d[59]), "+f"(d[60]), "+f"(d[61]), "+f"(d[62]), "+f"(d[63]), "+f"(d[64]), "+f"(d[65]), "+f"(d[66]), "+f"(d[67]), "+f"(d[68]), "+f"(d[69]), "+f"(d[70]), "+f"(d[71]), "+f"(d[72]), "+f"(d[73]), "+f"(d[74]), "+f"(d[75]), "+f"(d[76]), "+f"(d[77]), "+f"(d[78]), "+f"(d[79]), "+f"(d[80]), "+f"(d[81]), "+f"(d[82]), "+f"(d[83]), "+f"(d[84]), "+f"(d[85]), "+f"(d[86]), "+f"(d[87]), "+f"(d[88]), "+f"(d[89]), "+f"(d[90]), "+f"(d[91]), "+f"(d[92]), "+f"(d[93]), "+f"(d[94]), "+f"(d[95]), "+f"(d[96]), "+f"(d[97]), "+f"(d[98]), "+f"(d[99]), "+f"(d[100]), "+f"(d[101]), "+f"(d[102]), "+f"(d[103]), "+f"(d[104]), "+f"(d[105]), "+f"(d[106]), "+f"(d[107])
    : "l"(descA), "l"(descB), "r"(scaleD));
}
template<> __device__ __forceinline__ void wgmma_rs<64>(float (&d)[32], uint32_t a0, uint32_t a1, uint32_t a2, uint32_t a3, uint64_t descB, int scaleD) {
  asm volatile("{\n.reg .pred p;\nsetp.ne.b32 p, %37, 0;\n"
    "wgmma.mma_async.sync.aligned.m64n64k16.f32.bf16.bf16 {%0, %1, %2, %3, %4, %5, %6, %7, %8, %9, %10, %11, %12, %13, %14, %15, %16, %17, %18, %19, %20, %21, %22, %23, %24, %25, %26, %27, %28, %29, %30, %31}, {%32, %33, %34, %35}, %36, p, 1, 1, 1;\n}\n"
    : "+f"(d[0]), "+f"(d[1]), "+f"(d[2]), "+f"(d[3]), "+f"(d[4]), "+f"(d[5]), "+f"(d[6]), "+f"(d[7]), "+f"(d[8]), "+f"(d[9]), "+f"(d[10]), "+f"(d[11]), "+f"(d[12]), "+f"(d[13]), "+f"(d[14]), "+f"(d[15]), "+f"(d[16]), "+f"(d[17]), "+f"(d[18]), "+f"(d[19]), "+f"(d[20]), "+f"(d[21]), "+f"(d[22]), "+f"(d[23]), "+f"(d[24]), "+f"(d[25]), "+f"(d[26]), "+f"(d[27]), "+f"(d[28]), "+f"(d[29]), "+f"(d[30]), "+f"(d[31])
    : "r"(a0), "r"(a1), "r"(a2), "r"(a3), "l"(descB), "r"(scaleD));
}
template<> __device__ __forceinline__ void wgmma_rs<216>(float (&d)[108], uint32_t a0, uint32_t a1, uint32_t a2, uint32_t a3, uint64_t descB, int scaleD) {
  asm volatile("{\n.reg .pred p;\nsetp.ne.b32 p, %113, 0;\n"
    "wgmma.mma_async.sync.aligned.m64n216k16.f32.bf16.bf16 {%0, %1, %2, %3, %4, %5, %6, %7, %8, %9, %10, %11, %12, %13, %14, %15, %16, %17, %18, %19, %20, %21, %22, %23, %24, %25, %26, %27, %28, %29, %30, %31, %32, %33, %34, %35, %36, %37, %38, %39, %40, %41, %42, %43, %44, %45, %46, %47, %48, %49, %50, %51, %52, %53, %54, %55, %56, %57, %58, %59, %60, %61, %62, %63, %64, %65, %66, %67, %68, %69, %70, %71, %72, %73, %74, %75, %76, %77, %78, %79, %80, %81, %82, %83, %84, %85, %86, %87, %88, %89, %90, %91, %92, %93, %94, %95, %96, %97, %98, %99, %100, %101, %102, %103, %104, %105, %106, %107}, {%108, %109, %110, %111}, %112, p, 1, 1, 1;\n}\n"
    : "+f"(d[0]), "+f"(d[1]), "+f"(d[2]), "+f"(d[3]), "+f"(d[4]), "+f"(d[5]), "+f"(d[6]), "+f"(d[7]), "+f"(d[8]), "+f"(d[9]), "+f"(d[10]), "+f"(d[11]), "+f"(d[12]), "+f"(d[13]), "+f"(d[14]), "+f"(d[15]), "+f"(d[16]), "+f"(d[17]), "+f"(d[18]), "+f"(d[19]), "+f"(d[20]), "+f"(d[21]), "+f"(d[22]), "+f"(d[23]), "+f"(d[24]), "+f"(d[25]), "+f"(d[26]), "+f"(d[27]), "+f"(d[28]), "+f"(d[29]), "+f"(d[30]), "+f"(d[31]), "+f"(d[32]), "+f"(d[33]), "+f"(d[34]), "+f"(d[35]), "+f"(d[36]), "+f"(d[37]), "+f"(d[38]), "+f"(d[39]), "+f"(d[40]), "+f"(d[41]), "+f"(d[42]), "+f"(d[43]), "+f"(d[44]), "+f"(d[45]), "+f"(d[46]), "+f"(d[47]), "+f"(d[48]), "+f"(d[49]), "+f"(d[50]), "+f"(d[51]), "+f"(d[52]), "+f"(d[53]), "+f"(d[54]), "+f"(d[55]), "+f"(d[56]), "+f"(d[57]), "+f"(d[58]), "+f"(d[59]), "+f"(d[60]), "+f"(d[61]), "+f"(d[62]), "+f"(d[63]), "+f"(d[64]), "+f"(d[65]), "+f"(d[66]), "+f"(d[67]), "+f"(d[68]), "+f"(d[69]), "+f"(d[70]), "+f"(d[71]), "+f"(d[72]), "+f"(d[73]), "+f"(d[74]), "+f"(d[75]), "+f"(d[76]), "+f"(d[77]), "+f"(d[78]), "+f"(d[79]), "+f"(d[80]), "+f"(d[81]), "+f"(d[82]), "+f"(d[83]), "+f"(d[84]), "+f"(d[85]), "+f"(d[86]), "+f"(d[87]), "+f"(d[88]), "+f"(d[89]), "+f"(d[90]), "+f"(d[91]), "+f"(d[92]), "+f"(d[93]), "+f"(d[94]), "+f"(d[95]), "+f"(d[96]), "+f"(d[97]), "+f"(d[98]), "+f"(d[99]), "+f"(d[100]), "+f"(d[101]), "+f"(d[102]), "+f"(d[103]), "+f"(d[104]), "+f"(d[105]), "+f"(d[106]), "+f"(d[107])
    : "r"(a0), "r"(a1), "r"(a2), "r"(a3), "l"(descB), "r"(scaleD));
}

constexpr int TILE = 8192, HALF = 9 * TILE;
constexpr int SLOT = 16384;
constexpr int RING = 2 * HALF;
constexpr int OVF = RING + 5 * SLOT;
constexpr int TAB = OVF + 1024;
constexpr int BARS = TAB + 1024;
constexpr int SMEM_BYTES = BARS + 1024;
constexpr int WOA = 9216;
constexpr int B_FULL = BARS, B_FX = BARS + 56, B_AUX = BARS + 200, B_NB = BARS + 208, B_ROLE = BARS + 272, B_S1 = BARS + 280,
              B_ST = BARS + 288, B_EMPTY = BARS + 432, B_J = BARS + 488, B_XF = BARS + 496,
              B_QK = BARS + 504, B_RX = BARS + 512, B_SR = BARS + 528, B_OX = BARS + 536, B_HP = BARS + 552;
constexpr int S_ROLE = BARS + 568, S_EP = BARS + 572, S_WS = BARS + 576;

template <int V>
struct IC {
  static constexpr int value = V;
};
struct Maps {
  CUtensorMap x0, r, wq, wo, wg, wu, wd;
};

#define TA0(i)
#define TA(i)
#define TS(i)
#define TR(i)

__device__ __forceinline__ int tid_now() {
  int t;
  asm volatile("mov.u32 %0, %%tid.x;" : "=r"(t));
  return t;
}
__device__ __forceinline__ float quad_sum(float v) {
  v += __shfl_xor_sync(0xffffffffu, v, 1);
  return v + __shfl_xor_sync(0xffffffffu, v, 2);
}
__device__ __forceinline__ float inv_sd(float var) {
  float s, r;
  asm("sqrt.approx.ftz.f32 %0, %1;" : "=f"(s) : "f"(bf16r(bf16r(fmaxf(var, 0.f)) + 1e-5f)));
  asm("rcp.approx.ftz.f32 %0, %1;" : "=f"(r) : "f"(bf16r(s)));
  return r;
}
__device__ __forceinline__ float sum8(const uint4& v) {
  return ((bf_lo(v.x) + bf_hi(v.x)) + (bf_lo(v.y) + bf_hi(v.y))) + ((bf_lo(v.z) + bf_hi(v.z)) + (bf_lo(v.w) + bf_hi(v.w)));
}
__device__ __forceinline__ void warp_arrive(uint32_t bar) {
  __syncwarp();
  if ((tid_now() & 31) == 0) mbar_arrive(bar);
}
__device__ __forceinline__ void release_slot(uint32_t sb, int p, bool on = true) {
  asm volatile("{\n.reg .pred p;\nsetp.eq.u32 p, %1, 0;\n@p mbarrier.arrive.shared::cta.b64 _, [%0];\n}" ::"r"(sb + B_EMPTY + 8 * p),
               "r"((tid_now() & 31) | (on ? 0 : 1))
               : "memory");
}
#define RFENCE 1
__device__ __forceinline__ uint32_t stage_addr(uint32_t sb) {
  const int tid = tid_now(), lane = tid & 31;
  return sb + (tid >> 7) * HALF + ((tid >> 5) & 3) * 2048 + (lane & 15) * 128 + (((lane >> 4) ^ (lane & 7)) << 4);
}
__device__ __forceinline__ void stage_done(uint32_t sb, int a, int n) {
  if (!RFENCE) fence_proxy_async();
  __syncwarp();
  const int tid = tid_now();
  if ((tid & 31) < n) mbar_arrive(sb + B_ST + 72 * (tid >> 7) + 8 * (a + (tid & 31)));
}
template <int I0 = 0, int I1 = 4>
__device__ __forceinline__ void stage_tile(const float (&acc)[32], float m0, float c0, float m1, float c1, uint32_t sb, int a, int b, int n) {
  const uint32_t ad = stage_addr(sb) + a * TILE;
#pragma unroll
  for (int i = I0; i < I1; ++i)
    stsm_x4(ad ^ (i << 5), pack_bf16(fmaf(acc[8 * i], m0, c0), fmaf(acc[8 * i + 1], m0, c0)),
            pack_bf16(fmaf(acc[8 * i + 2], m1, c1), fmaf(acc[8 * i + 3], m1, c1)),
            pack_bf16(fmaf(acc[8 * i + 4], m0, c0), fmaf(acc[8 * i + 5], m0, c0)),
            pack_bf16(fmaf(acc[8 * i + 6], m1, c1), fmaf(acc[8 * i + 7], m1, c1)));
  if (n) stage_done(sb, b, n);
}

#define NLAYERS 2
#define X_EARLY 2
#define X_SCHED 0x1111111ull
#define PACE 2800
#define X_PF 0
#define DN_LATE 0
#define ST_END 5
#define GU_PF0 16
#define GU_PFN 16
#define R0_N 0
#define R1_N 4
#define PACE_R 1400
#define PACE0 4200
#define LAZY 2
#define Q_ST0 8
#define Q_ST1 8

__global__ void __cluster_dims__(2, 1, 1) __launch_bounds__(384, 1)
mega_kernel(const __grid_constant__ Maps mp, const __nv_bfloat16* __restrict__ x0, const __nv_bfloat16* __restrict__ wqkv,
            const __nv_bfloat16* __restrict__ wo, __nv_bfloat16* __restrict__ out, int small_gpc) {
  extern __shared__ __align__(1024) uint8_t smem[];
  const uint32_t sb = smem_u32(smem);
  const uint32_t rank = blockIdx.x & 1;
  const int warp = __shfl_sync(0xffffffffu, threadIdx.x >> 5, 0);
  TA0(63);
  uint32_t claim = 0, ep1 = 0;
  if (warp == 8) {
    if (threadIdx.x == 256 && rank == 0) {
      uint32_t tp;
      asm volatile("mov.u32 %0, %%smid;" : "=r"(tp));
      tp >>= 1;
      uint32_t pr = !small_gpc || tp < 32 ? tp & 7 : tp < 60 ? 1 + (tp - 32) % 7 : 0;
#pragma unroll 1
      for (int i = 0; i < 8; ++i, pr = (pr + 1) & 7) {
        claim = atomicAdd(&g_claim[pr], 1u);
        if (claim < 8) break;
      }
      claim = ((pr >> 2) * 8 + (claim & 7)) * 4 + (pr & 3);
    }
  } else {
    if (warp > 8) ep1 = g_epoch[blockIdx.x] + 1;
    if (elect_one()) {
      const uint32_t b0 = sb + BARS + 48 * (warp - (warp > 8));
      if (warp < 11) {
#pragma unroll
        for (int i = 0; i < 6; ++i) mbar_init(b0 + 8 * i, warp < 6 ? 1 : warp < 10 ? 4 : 8);
        if (warp == 5) mbar_expect_tx(sb + B_ROLE, 4);
      } else {
#pragma unroll
        for (int i = 0; i < 11; ++i) mbar_init(b0 + 8 * i, i < 3 ? 8 : i < 6 ? 4 : i < 7 ? 2 : 1);
      }
      asm volatile("fence.mbarrier_init.release.cluster;" ::: "memory");
      if (warp == 9) prefetch_map(&mp.x0);
      if (warp == 10) prefetch_map(&mp.wq);
    }
  }
  __syncwarp();
  cluster_arrive_relaxed();
  TA0(2);

  if (warp >= 8) {
    cluster_wait();
    if (threadIdx.x == 256 && rank == 0) {
#pragma unroll
      for (int r = 0; r < 2; ++r)
        asm volatile("st.async.weak.shared::cluster.mbarrier::complete_tx::bytes.u32 [%0], %1, [%2];" ::"r"(mapa(sb + S_ROLE, r)),
                     "r"(claim), "r"(mapa(sb + B_ROLE, r))
                     : "memory");
    }
    __syncwarp();
    asm volatile("setmaxnreg.dec.sync.aligned.u32 24;");
    mbar_wait(sb + B_ROLE, 0);
    const int role = __shfl_sync(0xffffffffu, lds_u32(sb + S_ROLE), 0);
    const int j = (role & 3) * 2 + rank, rb = role >> 2;
    ep1 = __shfl_sync(0xffffffffu, ep1, 0);
    TA0(59);
    if (warp == 8) {
      int p = 2;
      uint32_t ph = 1;
      const int f0 = j * 576;
      int xi = X_EARLY;
#pragma unroll 1
      for (int L = 0; L < NLAYERS; ++L) {
        {
          const int lane = tid_now() & 31;
          const __nv_bfloat16* src = wqkv + (size_t)lane * NQKV + 72 * j + (rank ? 0 : 64);
          const uint32_t dst = sb + RING + (lane >> 4) * 8192 + 6144 + (lane & 15) * 128;
#pragma unroll 1
          for (int s = 0; s < 18; ++s) {
            const uint32_t bar = sb + B_FULL + 8 * p;
            mbar_wait(bar + (B_EMPTY - B_FULL), ph);
            TR(s);
            if (elect_one()) tma_load_3d(sb + RING + p * SLOT, &mp.wq, bar, 72 * j + 8 * rank, 32 * s, 0);
            if (elect_one()) tma_load_3d(sb + RING + p * SLOT + 8192, &mp.wq, bar, 72 * j + 8 * rank, 32 * s + 16, 0);
#pragma unroll
            for (int c = 0; c < 3; ++c) cp_async16(dst + p * SLOT + ((c ^ (lane & 7)) << 4), src + c * 576);
            src += 32 * NQKV;
            cp_async_arrive(bar);
            __syncwarp();
            if (elect_one()) {
              mbar_expect_tx(bar, 12288);
              if (L == 0) {
#pragma unroll 1
                for (int e = (X_SCHED >> (2 * s)) & 3; e > 0; --e, ++xi)
                  tma_load_3d_mc(sb + rank * HALF + xi * TILE, &mp.x0, sb + B_FX + 72 * rank + 8 * xi, xi * 64, rb * 64 + rank * 32, 0);
                const int u = (s - GU_PF0) * 8 + (rb >> 1);
                if (s >= GU_PF0 && u < GU_PFN) tma_prefetch_2d((rb & 1) ? &mp.wu : &mp.wg, f0 + 64 * (u % 3), 64 * (u / 3));
              }
            }
            if (++p == 5) p = 0;
            if (p == 2) ph ^= 1;
          }
        }
#pragma unroll 1
        for (int s = 0; s < 5; ++s) {
          const int cx = s ? 64 * (2 * s - 1 + rank) : 0;
          mbar_wait(sb + B_EMPTY + 8 * s, ph);
          if (elect_one()) {
            if (s) tma_load_2d(sb + RING + (2 * s - 1) * WOA, &mp.wo, sb + B_FULL + 8 * s, cx, 72 * j);
            tma_load_2d(sb + RING + 2 * s * WOA, &mp.wo, sb + B_FULL + 8 * s, cx, 72 * (s ? j ^ 1 : j));
            mbar_expect_tx(sb + B_FULL + 8 * s, s ? 2 * WOA : WOA);
          }
          if (s == 1) ph ^= 1;
        }
        {
          int cx = f0, cy = 0;
#pragma unroll 1
          for (int n = 0; n < 81; ++n) {
            const uint32_t dst = sb + RING + p * SLOT, bar = sb + B_FULL + 8 * p;
            if (n == (rank ? R1_N : R0_N)) {
#pragma unroll 1
              for (int h = 1; h >= 0; --h) {
                mbar_wait(sb + B_ST + 72 * h + 8, 0);
                if (RFENCE) fence_proxy_async();
                if (elect_one()) tma_reduce_3d(&mp.r, sb + h * HALF + (1 + rank) * TILE, 64 + 64 * rank, rb * 64 + h * 32, 0);
              }
              bulk_commit();
            }
            mbar_wait(bar + (B_EMPTY - B_FULL), ph);
            if (elect_one()) tma_load_2d(dst, &mp.wg, bar, cx, cy);
            if (elect_one()) tma_load_2d(dst + 8192, &mp.wu, bar, cx, cy);
            if (elect_one()) mbar_expect_tx(bar, 16384);
            if (n == (rank ? R1_N : R0_N)) {
              bulk_wait<0>();
              if (elect_one()) mbar_arrive(sb + B_S1);
            }
            if (n < 26) {
              cx += 64;
              if (cx == f0 + 192) {
                cx = f0;
                cy += 64;
              }
            } else if ((cy += 64) == 576) {
              cy = 0;
              cx += 64;
            }
            if (++p == 5) p = 0;
            if (p == 2) ph ^= 1;
          }
        }
        {
          int cx = 0, cy = f0;
#pragma unroll 1
          for (int n = 35; n > -6; --n) {
            const uint32_t dst = p < 5 ? sb + RING + p * SLOT : sb + 2 * TILE + p * TILE, bar = sb + B_FULL + 8 * p;
            mbar_wait(bar + (B_EMPTY - B_FULL), ph);
            if (elect_one()) tma_load_2d(dst, &mp.wd, bar, cx, cy);
            if ((cy += 64) == f0 + 576) {
              cy = f0;
              cx += 64;
            }
            if (n > -5 && elect_one()) tma_load_2d(dst + (p < 5 ? 8192 : HALF), &mp.wd, bar, cx, cy);
            if (elect_one()) mbar_expect_tx(bar, n > -5 ? 16384 : 8192);
            if ((cy += 64) == f0 + 576) {
              cy = f0;
              cx += 64;
            }
            if (++p == (n > 1 ? 7 : 5)) p = 0;
            if (p == 2) ph ^= 1;
          }
        }
      }
    } else if (warp == 9) {
      auto fetch = [&](const CUtensorMap* map, uint32_t mask) {
        const int lane = tid_now() & 31;
        if ((mask >> lane) & 1)
          tma_load_3d_mc(sb + rank * HALF + lane * TILE, map, sb + B_FX + 72 * rank + 8 * lane, lane * 64, rb * 64 + rank * 32, 0);
        __syncwarp();
      };
      if ((tid_now() & 31) < 18) mbar_expect_tx(sb + B_FX + 8 * (tid_now() & 31), TILE);
      fetch(&mp.x0, (1u << X_EARLY) - 1);
      sts_u32(sb + S_EP, ep1);
      TA0(10);
      {
        const int lane = tid_now() & 31;
        mbar_wait(sb + B_J, 0);
        float2 c = make_float2(0.f, 0.f);
#pragma unroll
        for (int w = 0; w < 8; ++w) {
          const float2 v = lds_f2(sb + OVF + w * 256 + lane * 8);
          c.x += v.x;
          c.y += v.y;
        }
        if (blockIdx.x < 108) *reinterpret_cast<float2*>(g_csq + (blockIdx.x & 3) * NQKV + (blockIdx.x >> 2) * 64 + 2 * lane) = c;
        asm volatile("bar.arrive 6, 96;" ::: "memory");
        if (elect_one()) signal_release(&g_flag[FL_J]);
        TA0(11);
        poll_ge(&g_flag[FL_J], ep1 * 128u);
        TA0(12);
        if (blockIdx.x == 0 && lane < 8) g_claim[lane] = 0u;
        if (lane < 18) {
          const float4 w = ldg_cg_f4(g_wsum + 72 * j + 4 * lane);
          sts_u4(sb + S_WS + lane * 16, __float_as_uint(w.x), __float_as_uint(w.y), __float_as_uint(w.z), __float_as_uint(w.w));
        }
      }
#pragma unroll 1
      for (int n = 0; n < 2 * NLAYERS - 1; ++n) {
        if (n < NLAYERS) {
#pragma unroll 1
          for (int c = tid_now() & 31; c < 54; c += 32) {
            const int part = c / 18, i = c - 18 * part;
            const float* src = g_csq + part * 576 + 72 * j + 4 * (rank ? (i + 2) % 18 : i);
            float4 a = ldg_cg_f4(src), b = ldg_cg_f4(src + NQKV), d = ldg_cg_f4(src + 2 * NQKV);
            a.x += b.x; a.y += b.y; a.z += b.z; a.w += b.w;
            b = ldg_cg_f4(src + 3 * NQKV);
            a.x += b.x + d.x; a.y += b.y + d.y; a.z += b.z + d.z; a.w += b.w + d.w;
            const uint32_t h0 = pack_bf16(a.x, a.y), h1 = pack_bf16(a.z, a.w);
            const uint32_t ad = (i < 16 ? part * 256 + (((i >> 1) ^ (2 * part)) << 4) : 768 + ((part ^ 6) << 4)) + (i & 1) * 8;
            sts_f2(sb + OVF + ad, __uint_as_float(h0), __uint_as_float(h1));
            sts_f2(sb + OVF + (ad ^ 144), __uint_as_float(pack_bf16(a.x - bf_lo(h0), a.y - bf_hi(h0))),
                   __uint_as_float(pack_bf16(a.z - bf_lo(h1), a.w - bf_hi(h1))));
          }
          const int lane = tid_now() & 31;
          if (lane < 10) sts_u4(sb + OVF + 768 + (lane & 1) * 128 + (((3 + (lane >> 1)) ^ 6 ^ (lane & 1)) << 4), 0u, 0u, 0u, 0u);
          fence_proxy_async();
          warp_arrive(sb + B_AUX);
        }
        {
          const int lane = tid_now() & 31;
          const uint32_t bar = sb + B_FX + 8 * min(lane, 17);
#pragma unroll 1
          for (int it = 0; it < SPIN_MAX; ++it)
            if (__all_sync(0xffffffffu, mbar_test(bar, n & 1))) break;
          if (lane < 18) mbar_expect_tx(bar, TILE);
        }
        const unsigned int* fl = &g_flag[n * 512 + rb * 32 + rank * 16 + (tid_now() & 15)];
        if (LAZY) mbar_wait(sb + B_ST + 72 * rank, n & 1);
        uint32_t todo = 0x1FFu;
#pragma unroll 1
        for (int it = 0; todo && it < SPIN_MAX; ++it) {
          unsigned int v;
          asm volatile("ld.relaxed.gpu.global.u32 %0, [%1];" : "=r"(v) : "l"(fl) : "memory");
          const uint32_t ready = __ballot_sync(0xffffffffu, (int)(v - ep1 * 8u) >= 0) & todo;
          if (LAZY > 1 && (n & 1) && !ready && (todo & 0x7F)) __nanosleep(300);
          if (ready) {
            todo &= ~ready;
            fetch(&mp.r, ready);
          }
        }
      }
      uint32_t bid;
      asm volatile("mov.u32 %0, %%ctaid.x;" : "=r"(bid));
      if (elect_one()) g_epoch[bid] = ep1;
    } else {
      const int h = warp & 1;
      if (h) {
        const int lane = tid_now() & 31;
#pragma unroll 1
        for (int i = 0; i < 12; ++i) st_tagged(g_halo + (rb * 8 + j) * 384 + i * 32 + lane, 0u, 0u, 0u, 2 * ep1 - 1);
        if (lane < 16) st_tagged(g_stat + rb * 128 + (lane >> 3) * 64 + 8 * j + (lane & 7), 0u, 0u, 0u, 4 * ep1 - 1);
      }

      auto copy = [&](int hh, int c) {
        if (elect_one()) tma_store_3d(&mp.r, sb + hh * HALF + c * TILE, 64 * c, rb * 64 + hh * 32, 0);
        bulk_commit();
        bulk_wait<0>();
        __syncwarp();
        if (c < 3) asm volatile("fence.acq_rel.gpu;" ::: "memory");
      };
      float s1 = 0.f, s2 = 0.f;
      int kb = 0;
      uint32_t hn = 0;
      auto tile_stats = [&]() {
        const int lane = tid_now() & 31;
        const uint32_t ad = sb + h * HALF + kb * TILE + j * 1024 + (lane & 28) * 32 + (lane & 7) * 16;
        const uint4 u = lds_u4(ad), v = lds_u4(ad ^ 64);
        const uint32_t w[8] = {u.x, u.y, u.z, u.w, v.x, v.y, v.z, v.w};
        float a = 0.f, b = 0.f;
#pragma unroll
        for (int e = 0; e < 8; ++e) {
          const float lo = bf_lo(w[e]), hi = bf_hi(w[e]);
          s1 += lo;
          a += hi;
          s2 = fmaf(lo, lo, s2);
          b = fmaf(hi, hi, b);
        }
        s1 += a;
        s2 += b;
        ++kb;
      };
      unsigned int* fl = &g_flag[rb * 32];
#pragma unroll 1
      for (int n = 0; n < 2 * NLAYERS; ++n, fl += 512) {
        const int L = n >> 1;
        (void)L;
        {
          const int lane = tid_now() & 31;
#pragma unroll 1
          while (kb < 8 + (n & 1)) {
            mbar_wait(sb + B_FX + 72 * h + 8 * kb, n & 1);
            tile_stats();
            if (n == 0 && kb == j + 1) copy(h, j);
          }
          s1 = quad_sum(s1) * ((n & 1) ? 1.0f / DM : 1.0f / 512);
          s2 = fmaf(s1 * s1, (n & 1) ? -576.f : -512.f, quad_sum(s2));
          if (n & 1) {
            s2 = inv_sd(s2 * (1.0f / DM));
            s2 *= s2;
          }
          uint4* gs = g_stat + rb * 128 + h * 64;
          const uint32_t tag = 4 * ep1 + n;
          if ((lane & 3) == 0) st_tagged(gs + 8 * j + (lane >> 2), __float_as_uint(s1) & ~128u, __float_as_uint(s2) & ~128u, 0u, tag);
          s1 = s2 = 0.f;
          kb = 0;
          TA(14 + (n & 1) * 2);
          uint4 u, v;
#pragma unroll 1
          for (int it = 0; it < SPIN_MAX; ++it) {
            u = ld_tagged(gs + 2 * lane);
            v = ld_tagged(gs + 2 * lane + 1);
            if (__all_sync(0xffffffffu, u.w == tag && v.w == tag)) break;
          }
          if (n == 0) named_bar_sync(6, 96);
          if (n & 1) {
            sts_u32(sb + TAB + h * 512 + lane * 16 + 4, u.y);
            sts_u32(sb + TAB + h * 512 + lane * 16 + 12, v.y);
          } else {
            sts_u4(sb + TAB + h * 512 + lane * 16, u.x, u.y, v.x, v.y);
            fence_proxy_async();
          }
          warp_arrive(sb + B_SR);
          TA(15 + (n & 1) * 2);
        }
        if (!((n & 1) | h)) {
          const int lane = tid_now() & 31;
          const uint32_t dst = sb + (2 - rank) * TILE;
          mbar_wait(sb + B_QK, L);
          TA(18);
          if (rb) {
            auto attempt = [&](uint32_t b) {
              if (elect_one()) {
                mbar_expect_tx(sb + B_HP + 8 * b, 6144);
                bulk_load(dst, g_halo + (rb * 8 - 8 + j) * 384, 6144, sb + B_HP + 8 * b);
              }
            };
            attempt(hn & 1);
            __nanosleep(100);
#pragma unroll 1
            for (int it = 0; it < SPIN_MAX; ++it) {
              attempt(~hn & 1);
              mbar_wait(sb + B_HP + 8 * (hn & 1), (hn >> 1) & 1);
              ++hn;
              uint32_t bad = 0;
#pragma unroll
              for (int i = 0; i < 12; ++i) bad |= lds_u32(dst + lane * 16 + 12 + i * 512) ^ (2 * ep1 + L);
              if (__all_sync(0xffffffffu, bad == 0)) break;
            }
          } else {
#pragma unroll 1
            for (int i = 0; i < 12; ++i) sts_u4(dst + lane * 16 + i * 512, 0u, 0u, 0u, 0u);
            __syncwarp();
          }
          if (lane < 2) mbar_arrive(sb + B_NB + 16 * lane);
          TA(19);
          if (rb) {
            mbar_wait(sb + B_HP + 8 * (hn & 1), (hn >> 1) & 1);
            ++hn;
          }
        }
        if (n == 0 && h && (j & 5) == 0) {
          mbar_wait(sb + B_FX + 36 * j + 64, 0);
          copy(j >> 1, 8);
        }
        auto send = [&](int hh, int c) {
          TA(20 + (n & 1) * 20 + c);
          if (RFENCE) fence_proxy_async();
          if (elect_one()) tma_reduce_3d(&mp.r, sb + hh * HALF + c * TILE, 64 * c, rb * 64 + hh * 32, 0);
          bulk_commit();
        };
        if (!(n & 1)) {
          uint32_t tnext, t;
#pragma unroll 1
          for (int i = 0; i < 5; ++i) {
            const int c = i ? 2 * i - 1 + rank : 0;
            if (i == 1) {
              TA(20 + c);
              if (h) {
                mbar_wait(sb + B_S1, L);
                if (elect_one()) {
                  signal_release(fl + 16 + c, 2);
                  signal_relaxed(fl + c, 2);
                }
              }
              TA(30 + c);
              continue;
            }
            mbar_wait(sb + B_ST + 72 * h + 8 * i, 0);
            while (true) {
              asm volatile("mov.u32 %0, %%clock;" : "=r"(t));
              if (i == 0 || (int)(t - tnext) >= 0) break;
              __nanosleep(40);
            }
            tnext = i ? tnext + PACE : t + PACE0 + rank * PACE_R;
            if (i == (n ? 4 : 2)) {
              mbar_wait(sb + B_FX, 1);
              mbar_wait(sb + B_FX + 72, 1);
            }
            send(h, c);
            bulk_wait<0>();
            if (elect_one()) signal_release(fl + 16 * h + c, i ? 2 : 1);
            TA(30 + c);
          }
        } else {
#pragma unroll 1
          for (int a = h ^ 1; a < 9; a += 2) {
            mbar_wait(sb + B_ST + 72 + 8 * a, 1);
            send(1, a);
            mbar_wait(sb + B_ST + 8 * a, 1);
            send(0, a);
            if (n < 2 * NLAYERS - 1) {
              bulk_wait<0>();
              if (elect_one()) {
                signal_release(fl + 16 + a);
                signal_relaxed(fl + a);
              }
              TA(50 + a);
#pragma unroll 1
              while (kb < min(a - 1, ST_END)) {
                mbar_wait(sb + B_FX + 72 * h + 8 * kb, 0);
                tile_stats();
              }
            }
          }
          bulk_wait<0>();
        }
      }
    }
  } else {
    {
      const int t = threadIdx.x, lane = t & 31;
      uint4 sq[5], so[3];
      if (t < 16 * X_PF) asm volatile("prefetch.global.L2 [%0];" ::"l"(x0 + (size_t)(blockIdx.x * 16 + (t & 15)) * DM + (t >> 4) * 64));
#pragma unroll
      for (int i = 0; i < 5; ++i)
        sq[i] = ldg_u4(wqkv + (size_t)((blockIdx.x & 3) + (t >> 3) * 4 + 128 * i) * NQKV + (blockIdx.x >> 2) * 64 + (t & 7) * 8,
                       blockIdx.x < 108 && (i < 4 || t < 128));
#pragma unroll
      for (int i = 0; i < 3; ++i)
        so[i] = ldg_u4(wo + (size_t)((blockIdx.x - 32) * 6 + warp) * DM + (i * 32 + lane) * 8,
                       blockIdx.x >= 32 && warp < 6 && (i < 2 || lane < 8));
      asm volatile("setmaxnreg.inc.sync.aligned.u32 240;");
      float c[8];
#pragma unroll
      for (int e = 0; e < 8; ++e) c[e] = 0.f;
#pragma unroll
      for (int i = 0; i < 5; ++i) {
        c[0] += bf_lo(sq[i].x); c[1] += bf_hi(sq[i].x); c[2] += bf_lo(sq[i].y); c[3] += bf_hi(sq[i].y);
        c[4] += bf_lo(sq[i].z); c[5] += bf_hi(sq[i].z); c[6] += bf_lo(sq[i].w); c[7] += bf_hi(sq[i].w);
      }
#pragma unroll
      for (int n = 4; n >= 2; n >>= 1) {
        const bool up = lane & (4 * n);
#pragma unroll
        for (int e = 0; e < n; ++e) c[e] = (up ? c[e + n] : c[e]) + __shfl_xor_sync(0xffffffffu, up ? c[e] : c[e + n], 4 * n);
      }
      sts_f2(sb + OVF + warp * 256 + (lane & 7) * 32 + (lane & 24), c[0], c[1]);
      float r = sum8(so[0]) + sum8(so[1]) + sum8(so[2]);
#pragma unroll
      for (int o = 1; o < 32; o <<= 1) r += __shfl_xor_sync(0xffffffffu, r, o);
      if (lane == 0 && blockIdx.x >= 32 && warp < 6) g_wsum[(blockIdx.x - 32) * 6 + warp] = r;
      cluster_wait();
      warp_arrive(sb + B_J);
      TA0(13);
    }
#pragma unroll 1
    for (uint32_t L = 0; L < NLAYERS; ++L) {
      {
        const int wg = warp >> 2;
        float acc[108];
        const uint32_t da0 = desc_lo_a(sb + wg * HALF), db0 = desc_lo_b(sb + RING, 2048);
        int p = 2;
        uint32_t ph = L;
        auto step = [&](int kb, auto U, auto FIRST) {
          constexpr int u = decltype(U)::value, first = decltype(FIRST)::value == 1;
          mbar_wait(sb + B_FULL + 8 * p, ph);
          wgmma_fence();
#pragma unroll
          for (int k = 0; k < 2; ++k)
            wgmma_ss<216>(acc, desc_from_lo(da0 + kb * 512 + u * 4 + k * 2), desc_from_lo(db0 + p * 1024 + k * 512), !first || u || k);
          wgmma_commit();
          if (decltype(FIRST)::value == 2 && kb == 8 && wg) asm volatile("bar.arrive 5, 256;" ::: "memory");
          if (!first || u) {
            wgmma_wait<1>();
            release_slot(sb, p == 0 ? 4 : p - 1);
          }
          if (++p == 5) p = 0;
          if (p == 2) ph ^= 1;
        };
        mbar_wait(sb + B_FX + 72 * wg, 0);
        TR(1);
        step(0, IC<0>{}, IC<1>{});
        step(0, IC<1>{}, IC<1>{});
        int kb = 1;
#pragma unroll 1
        for (; kb < (wg ? Q_ST1 : Q_ST0); ++kb) {
          mbar_wait(sb + B_FX + 72 * wg + 8 * kb, 0);
          TR(1 + kb);
          step(kb, IC<0>{}, IC<0>{});
          step(kb, IC<1>{}, IC<0>{});
        }
        const int tid = tid_now(), lane = tid & 31, g = lane >> 2, q = lane & 3;
        float2 st0, st1;
        {
          float s1[2], s2[2];
          if (lane == 0 && wg == 0) mbar_arrive(sb + B_QK);
          mbar_wait(sb + B_FX + 72 * wg + 64, 0);
#pragma unroll
          for (int r = 0; r < 2; ++r) {
            const uint32_t ad = sb + wg * HALF + 8 * TILE + (warp & 3) * 2048 + r * 1024 + g * 128 + (lane & 7) * 16;
            const uint4 u = lds_u4(ad), v = lds_u4(ad ^ 64);
            const uint32_t w[8] = {u.x, u.y, u.z, u.w, v.x, v.y, v.z, v.w};
            float a = 0.f, b = 0.f, c = 0.f, d = 0.f;
#pragma unroll
            for (int e = 0; e < 8; ++e) {
              const float lo = bf_lo(w[e]), hi = bf_hi(w[e]);
              a += lo;
              b += hi;
              c = fmaf(lo, lo, c);
              d = fmaf(hi, hi, d);
            }
            s1[r] = quad_sum(a + b) * (1.0f / 64);
            s2[r] = fmaf(s1[r] * s1[r], -64.f, quad_sum(c + d));
          }
          mbar_wait(sb + B_SR, 0);
          mbar_wait(sb + B_AUX, L);
          st0 = lds_f2(sb + TAB + (warp * 16 + g) * 8);
          st1 = lds_f2(sb + TAB + (warp * 16 + g) * 8 + 64);
          s1[0] -= st0.x;
          s1[1] -= st1.x;
          st0.x = fmaf(s1[0], 1.0f / 9, st0.x);
          st1.x = fmaf(s1[1], 1.0f / 9, st1.x);
          st0.y = fmaf(s1[0] * s1[0], 512.f / 9, st0.y + s2[0]);
          st1.y = fmaf(s1[1] * s1[1], 512.f / 9, st1.y + s2[1]);
          if (wg == 0) named_bar_sync(5, 256);
        }
        wgmma_fence();
        wgmma_rs<216>(acc, q ? 0u : pack_bf16(-st0.x, -st0.x), q ? 0u : pack_bf16(-st1.x, -st1.x), 0u, 0u, desc_sbo(desc_lo_b(sb + OVF, 256), 0), 1);
        wgmma_commit();
#pragma unroll 1
        for (; kb < 9; ++kb) {
          mbar_wait(sb + B_FX + 72 * wg + 8 * kb, 0);
          TR(1 + kb);
          step(kb, IC<0>{}, IC<0>{});
          step(kb, IC<1>{}, IC<2>{});
        }
        TR(10);
        st0.y = inv_sd(st0.y * (1.0f / DM));
        st1.y = inv_sd(st1.y * (1.0f / DM));
        const uint32_t ep1 = lds_u32(sb + S_EP), role = lds_u32(sb + S_ROLE);
        const bool first = (warp & 5) == 0 && role < 4;
        const bool e0 = 2 * q > g, e1 = 2 * q + 1 > g;
        float fs[2][2], fp[2][2], fb[2];
        {
          const float k0 = __shfl_sync(0xffffffffu, st0.y, 8 * q), k1 = __shfl_sync(0xffffffffu, st0.y, 8 * q + 4);
          const float c = 0.23570226039551584f * 1.4426950408889634f;
          fp[0][0] = e0 ? 1.f : k0;
          fp[0][1] = e1 ? 1.f : k1;
          fp[1][0] = e0 ? k0 : 1.f;
          fp[1][1] = e1 ? k1 : 1.f;
#pragma unroll
          for (int i = 0; i < 4; ++i) fs[i >> 1][i & 1] = fp[i >> 1][i & 1] * ((i >> 1) ? st1.y : st0.y) * c;
          fb[0] = first && e0 ? -INFINITY : 0.f;
          fb[1] = first && e1 ? -INFINITY : 0.f;
        }
        wgmma_wait<0>();
        release_slot(sb, 4);
        TS(1);
        uint32_t Q[2][9], K[3][9], V[3][9];
        auto pack = [&](auto R, auto UP) {
#pragma unroll
          for (int i = 0; i < 9; ++i) {
            const int c = (i + 9 - decltype(R)::value) % 9, jq = c < 8 ? 4 * c : 96, jk = c < 8 ? 32 + 4 * c : 100, jv = c < 8 ? 64 + 4 * c : 104;
            if (decltype(UP)::value) {
              K[2][i] = pack_bf16(acc[jk + 2] * st1.y, acc[jk + 3] * st1.y);
              V[2][i] = movm(pack_bf16(acc[jv + 2] * st1.y, acc[jv + 3] * st1.y));
            } else {
              Q[0][i] = pack_bf16(acc[jq], acc[jq + 1]);
              Q[1][i] = pack_bf16(acc[jq + 2], acc[jq + 3]);
              K[1][i] = pack_bf16(acc[jk], acc[jk + 1]);
              V[1][i] = movm(pack_bf16(acc[jv], acc[jv + 1]));
            }
          }
        };
        if (rank) pack(IC<1>{}, IC<1>{});
        else pack(IC<0>{}, IC<1>{});
        {
          const int sw = (warp & 1) ? warp + 3 : warp + 1;
          if (sw >= 8) {
            uint4* hp = g_halo + (role * 2 + rank) * 384 + (warp & 2) * 96 + lane;
#pragma unroll
            for (int i = 0; i < 6; ++i) {
              const uint32_t(&d)[9] = i < 3 ? K[2] : V[2];
              st_tagged(hp + i * 32, d[3 * (i % 3)], d[3 * (i % 3) + 1], d[3 * (i % 3) + 2], 2 * ep1 + L);
            }
          } else {
            const uint32_t ad = sb + (sw >> 2) * HALF + (2 + 2 * (sw & 1) - rank) * TILE + (sw & 2) * 1536 + lane * 16;
#pragma unroll
            for (int i = 0; i < 6; ++i) {
              const uint32_t(&d)[9] = i < 3 ? K[2] : V[2];
              sts_u4(ad + i * 512, d[3 * (i % 3)], d[3 * (i % 3) + 1], d[3 * (i % 3) + 2], d[3 * (i % 3) + 2]);
            }
            __syncwarp();
            if (lane == 0) mbar_arrive(sb + B_NB + 8 * sw);
          }
        }
        if (lane == 0) {
          if (!(warp & 3)) mbar_expect_tx(sb + B_OX + 8 * wg, 10240);
          mbar_arrive_cluster(mapa(sb + B_RX + 8 * wg, rank ^ 1));
        }
        if (rank) pack(IC<1>{}, IC<0>{});
        else pack(IC<0>{}, IC<0>{});
        uint32_t qf[4][2], ql[4][2];
        float sc[4][3][4];
        auto logits = [&](int t) {
#pragma unroll
          for (int h = 0; h < 4; ++h) {
            mma_1688(sc[h][t], ql[h][0], ql[h][1], K[t][2 * h + 2]);
            mma_16816(sc[h][t], qf[h][0], qf[h][1], Q[0][2 * h + 1], Q[1][2 * h + 1], K[t][2 * h], K[t][2 * h + 1]);
          }
        };
#pragma unroll
        for (int i = 0; i < 8; ++i) {
          qf[i >> 1][i & 1] = q >= (i >> 1) ? Q[i & 1][i & 6] : 0u;
          ql[i >> 1][i & 1] = q <= (i >> 1) ? Q[i & 1][(i & 6) + 2] : 0u;
        }
        logits(1);
        logits(2);
        float2 ws[9];
#pragma unroll
        for (int i = 0; i < 9; ++i) ws[i] = lds_f2(sb + S_WS + i * 32 + 8 * q);
        uint32_t of[9][2];
        float o0[9][2];
        auto rows = [&](auto R, float(&o)[9][2]) {
          constexpr int r = decltype(R)::value;
          float pr[4][2], mx[4];
#pragma unroll
          for (int h = 0; h < 4; ++h) {
            pr[h][0] = fmaf(e0 ? sc[h][r][2 * r] : sc[h][r + 1][2 * r], fs[r][0], r ? 0.f : fb[0]);
            pr[h][1] = fmaf(e1 ? sc[h][r][2 * r + 1] : sc[h][r + 1][2 * r + 1], fs[r][1], r ? 0.f : fb[1]);
            mx[h] = fmaxf(pr[h][0], pr[h][1]);
          }
#pragma unroll
          for (int i = 0; i < 8; ++i) mx[i & 3] = fmaxf(mx[i & 3], __shfl_xor_sync(0xffffffffu, mx[i & 3], 1 + (i >> 2)));
#pragma unroll
          for (int h = 0; h < 4; ++h) {
#pragma unroll
            for (int e = 0; e < 2; ++e) asm("ex2.approx.ftz.f32 %0, %1;" : "=f"(pr[h][e]) : "f"(pr[h][e] - mx[h]));
            mx[h] = pr[h][0] + pr[h][1];
            pr[h][0] *= fp[r][0];
            pr[h][1] *= fp[r][1];
          }
#pragma unroll
          for (int i = 0; i < 8; ++i) mx[i & 3] += __shfl_xor_sync(0xffffffffu, mx[i & 3], 1 + (i >> 2));
          const uint32_t me = (e0 ? 0xFFFFu : 0u) | (e1 ? 0xFFFF0000u : 0u);
          uint32_t pp[4];
#pragma unroll
          for (int h = 0; h < 4; ++h) {
            float inv;
            asm("rcp.approx.ftz.f32 %0, %1;" : "=f"(inv) : "f"(mx[h]));
            pp[h] = pack_bf16(pr[h][0] * inv, pr[h][1] * inv);
          }
#pragma unroll
          for (int i = 0; i < 9; ++i) {
            const int h = i < 4 ? 0 : i < 5 ? 1 : 2;
            float d[4];
            mma_16816_z(d, pp[h] & me, pp[h + 1] & me, pp[h] & ~me, pp[h + 1] & ~me, V[r][i], V[r + 1][i]);
            const bool up = i == 2 * h + 2 ? q > h : i > 2 * h + 2;
            o[i][0] = up ? d[2] : d[0];
            o[i][1] = up ? d[3] : d[1];
            of[i][r] = pack_bf16(o[i][0], o[i][1]);
          }
        };
        auto shift = [&](const float(&o)[9][2], float mean) {
          float a = 0.f, b = 0.f, c = 0.f;
#pragma unroll
          for (int i = 0; i < 3; ++i) {
            a = fmaf(o[i][0], ws[i].x, fmaf(o[i][1], ws[i].y, a));
            b = fmaf(o[i + 3][0], ws[i + 3].x, fmaf(o[i + 3][1], ws[i + 3].y, b));
            c = fmaf(o[i + 6][0], ws[i + 6].x, fmaf(o[i + 6][1], ws[i + 6].y, c));
          }
          return fmaf(quad_sum(a + b + c), 1.0f / DM, mean * 0.125f);
        };
        rows(IC<1>{}, o0);
        float sh1 = shift(o0, st1.x);
        mbar_wait(sb + B_FULL, L ^ 1);
        mbar_wait(sb + B_NB + 8 * warp, L);
#pragma unroll
        for (int i = 0; i < 6; ++i) {
          const uint4 u = lds_u4(sb + wg * HALF + (2 + 2 * (warp & 1) - rank) * TILE + (warp & 2) * 1536 + lane * 16 + i * 512);
          uint32_t(&d)[9] = i < 3 ? K[0] : V[0];
          d[3 * (i % 3)] = u.x;
          d[3 * (i % 3) + 1] = u.y;
          d[3 * (i % 3) + 2] = u.z;
        }
        TS(3);
        logits(0);
        rows(IC<0>{}, o0);
        TS(5);
        float wa[3][32];
        const uint32_t dw0 = desc_lo_b(sb + RING, 0);
        wgmma_fence();
#pragma unroll
        for (int k = 0; k < 5; ++k)
          wgmma_rs<64>(wa[0], of[2 * k][0], of[2 * k][1], k < 4 ? of[2 * k + 1][0] : 0u, k < 4 ? of[2 * k + 1][1] : 0u,
                       desc_sbo(dw0 + k * 128, k < 4 ? 1024 : 0), k);
        wgmma_commit();
        const uint32_t xa = sb + wg * HALF + 3 * TILE + (warp & 3) * 2048 + lane * 16;
        const uint32_t xr = mapa(xa + (rank ^ 1) * TILE, rank ^ 1), xb = mapa(sb + B_OX + 8 * wg, rank ^ 1);
        mbar_wait(sb + B_RX + 8 * wg, L);
#pragma unroll
        for (int i = 0; i < 4; ++i) st_async_u4(xr + i * 512, xb, of[2 * i][0], of[2 * i][1], of[2 * i + 1][0], of[2 * i + 1][1]);
        float sh0 = shift(o0, st0.x);
        st_async_u4(xr + 2 * TILE, xb, of[8][0], of[8][1], __float_as_uint(sh0), __float_as_uint(sh1));
        wgmma_wait<0>();
        stage_tile(wa[0], 1.f, -sh0, 1.f, -sh1, sb, 0, 0, 1);
        TS(6);
        uint4 xv[5];
        auto issue = [&](auto I, auto PART) {
          constexpr int i = decltype(I)::value, part = decltype(PART)::value;
          const uint32_t lo = dw0 + (2 * i - 1) * (WOA / 16);
          if (part & 1) mbar_wait(sb + B_FULL + 8 * i, (i == 1) ^ L);
          wgmma_fence();
          if (part & 1) {
#pragma unroll
            for (int k = 0; k < 4; ++k)
              wgmma_rs<64>(wa[i % 3], of[2 * k][0], of[2 * k][1], of[2 * k + 1][0], of[2 * k + 1][1], desc_sbo(lo + k * 128, 1024), k);
          }
          if (part & 2) {
            wgmma_rs<64>(wa[i % 3], of[8][0], of[8][1], xv[4].x, xv[4].y, desc_sbo(lo + 512, WOA), 1);
#pragma unroll
            for (int k = 0; k < 4; ++k)
              wgmma_rs<64>(wa[i % 3], xv[k].x, xv[k].y, xv[k].z, xv[k].w, desc_sbo(lo + WOA / 16 + k * 128, 1024), 1);
          }
          wgmma_commit();
        };
        issue(IC<1>{}, IC<1>{});
        if (q < 2) sts_u32(sb + TAB + (warp * 16 + g + 8 * q) * 8, __float_as_uint(q ? sh1 : sh0));
        mbar_wait(sb + B_OX + 8 * wg, L);
#pragma unroll
        for (int i = 0; i < 5; ++i) xv[i] = lds_u4(xa + rank * TILE + (i < 4 ? i * 512 : 2 * TILE));
        sh0 += __uint_as_float(xv[4].z);
        sh1 += __uint_as_float(xv[4].w);
        TS(4);
        issue(IC<1>{}, IC<2>{});
        wgmma_wait<0>();
        release_slot(sb, 0);
        stage_tile(wa[1], 1.f, -sh0, 1.f, -sh1, sb, 1 + rank, 1, 1);
        issue(IC<2>{}, IC<3>{});
        issue(IC<3>{}, IC<3>{});
        wgmma_wait<1>();
        release_slot(sb, 1);
        issue(IC<4>{}, IC<3>{});
        stage_tile(wa[2], 1.f, -sh0, 1.f, -sh1, sb, 3 + rank, 0, 0);
        wgmma_wait<1>();
        release_slot(sb, 2);
        stage_tile(wa[0], 1.f, -sh0, 1.f, -sh1, sb, 5 + rank, 0, 0);
        wgmma_wait<0>();
        release_slot(sb, 3);
        release_slot(sb, 4);
        stage_tile(wa[1], 1.f, -sh0, 1.f, -sh1, sb, 7 + rank, 2, 7);
        TS(7);
      }
      uint32_t hreg[9][16];
      {
        const int wg = warp >> 2;
        float acc[64];
        int p = 0;
        uint32_t ph = L;
        const uint32_t da0 = desc_lo_a(sb + wg * HALF), db0 = desc_lo_b(sb + RING, 8192);
        float prod[32];
        {
          float acc0[64], acc1[64], acc2[64];
#pragma unroll
          for (int i = 0; i < 64; ++i) acc0[i] = acc1[i] = acc2[i] = 0.f;
          auto step = [&](float(&d)[64], int kb, bool rel) {
            mbar_wait(sb + B_FULL + 8 * p, ph);
            wgmma_fence();
#pragma unroll
            for (int k = 0; k < 4; ++k)
              wgmma_ss<128>(d, desc_from_lo(da0 + kb * 512 + k * 2), desc_from_lo(db0 + p * 1024 + k * 128), 1);
            wgmma_commit();
            wgmma_wait<1>();
            release_slot(sb, p == 0 ? 4 : p - 1, rel);
            if (++p == 5) p = 0;
            if (p == 2) ph ^= 1;
          };
#pragma unroll 1
          for (int kb = 0; kb < 9; ++kb) {
            mbar_wait(sb + B_FX + 72 * wg + 8 * kb, 1);
            if (kb == 0) TS(9);
            TR(16 + kb);
            step(acc0, kb, kb > 0);
            step(acc1, kb, true);
            step(acc2, kb, true);
          }
#pragma unroll
          for (int i = 0; i < 16; ++i) {
            hreg[0][i] = pack_bf16(acc0[2 * i] * acc0[32 + 2 * i], acc0[2 * i + 1] * acc0[33 + 2 * i]);
            hreg[1][i] = pack_bf16(acc1[2 * i] * acc1[32 + 2 * i], acc1[2 * i + 1] * acc1[33 + 2 * i]);
          }
          mbar_wait(sb + B_FULL + 8 * p, ph);
          wgmma_wait<0>();
#pragma unroll
          for (int i = 0; i < 32; ++i) prod[i] = acc2[i] * acc2[32 + i];
        }
#pragma unroll
        for (int t = 2; t < 8; ++t)
#pragma unroll
          for (int i = 0; i < 16; ++i) hreg[t][i] = 0u;
        TS(10);
#pragma unroll 1
        for (int t = 3; t < 9; ++t) {
          wgmma_fence();
#pragma unroll
          for (int k = 0; k < 4; ++k)
            wgmma_ss<128>(acc, desc_from_lo(da0 + k * 2), desc_from_lo(db0 + p * 1024 + k * 128), k != 0);
          wgmma_commit();
          release_slot(sb, p == 0 ? 4 : p - 1);
#pragma unroll
          for (int i = 0; i < 32; ++i) asm volatile("" : "+f"(prod[i]));
#pragma unroll
          for (int i = 0; i < 16; ++i) hreg[8][i] = pack_bf16(prod[2 * i], prod[2 * i + 1]);
          if (++p == 5) p = 0;
          if (p == 2) ph ^= 1;
#pragma unroll 1
          for (int kb = 1; kb < 9; ++kb) {
            mbar_wait(sb + B_FULL + 8 * p, ph);
            wgmma_fence();
#pragma unroll
            for (int k = 0; k < 4; ++k)
              wgmma_ss<128>(acc, desc_from_lo(da0 + kb * 512 + k * 2), desc_from_lo(db0 + p * 1024 + k * 128), 1);
            wgmma_commit();
            if (kb == 1) {
#pragma unroll
              for (int tt = 2; tt < 8; ++tt)
                if (t == tt + 1) {
#pragma unroll
                  for (int i = 0; i < 16; ++i) asm volatile("mov.b32 %0, %1;" : "=r"(hreg[tt][i]) : "r"(hreg[8][i]));
                }
            }
            wgmma_wait<1>();
            release_slot(sb, p == 0 ? 4 : p - 1);
            if (++p == 5) p = 0;
            if (p == 2) ph ^= 1;
          }
          mbar_wait(sb + B_FULL + 8 * p, ph);
          wgmma_wait<0>();
#pragma unroll
          for (int i = 0; i < 32; ++i) prod[i] = acc[i] * acc[32 + i];
          TR(32 + t);
        }
#pragma unroll
        for (int i = 0; i < 16; ++i) hreg[8][i] = pack_bf16(prod[2 * i], prod[2 * i + 1]);
      }
      TS(11);
      {
        float accA[32], accB[32];
#pragma unroll
        for (int i = 16; i < 32; ++i) accB[i] = 0.f;
        int p = 1;
        uint32_t ph = L;
        const uint32_t db0 = desc_lo_b(sb + RING, 8192);
        int prev = 0, left = 35;
        auto stage = [&](auto S, auto NU, bool rel) {
          constexpr int s = decltype(S)::value;
          mbar_wait(sb + B_FULL + 8 * p, ph ^ (p >= 5));
          const uint32_t dlo = p < 5 ? db0 + p * 1024 : db0 - RING / 16 + 1024 + p * 512, dv = p < 5 ? 512 : HALF / 16;
          wgmma_fence();
#pragma unroll
          for (int v = 0; v < decltype(NU)::value; ++v) {
            const int u = 2 * s + v, kq = u % 9;
#pragma unroll
            for (int k = 0; k < 4; ++k)
              wgmma_rs<64>(u >= 9 ? accB : accA, hreg[kq][4 * k], hreg[kq][4 * k + 1], hreg[kq][4 * k + 2], hreg[kq][4 * k + 3],
                           desc_from_lo(dlo + v * dv + k * 128), (kq | k) != 0);
          }
          wgmma_commit();
          if (rel) {
            wgmma_wait<1>();
            release_slot(sb, prev, prev < 5 || left > 2);
          }
          prev = p;
          --left;
          if (++p == (left > 0 ? 7 : 5)) p = 0;
          if (p == 2) ph ^= 1;
        };
        stage(IC<0>{}, IC<2>{}, false);
        release_slot(sb, 0);
        mbar_wait(sb + B_SR, 1);
        release_slot(sb, 5);
        release_slot(sb, 6);
        const uint32_t ta = sb + TAB + warp * 128 + (tid_now() & 28) * 2;
        const float2 t0 = lds_f2(ta), t1 = lds_f2(ta + 64);
        const float m0 = t0.y, c0 = t0.x, m1 = t1.y, c1 = t1.x;
#pragma unroll 1
        for (int i = 0; i < 4; ++i) {
          stage(IC<1>{}, IC<2>{}, true);
          if (i) stage_tile<2, 4>(accB, m0, c0, m1, c1, sb, 2 * i - 1, 0, 0);
          stage(IC<2>{}, IC<2>{}, true);
          if (i) stage_done(sb, 2 * i - 1, 1);
          stage(IC<3>{}, IC<2>{}, true);
          stage(IC<4>{}, IC<2>{}, true);
          stage(IC<5>{}, IC<2>{}, true);
          stage_tile<0, 2>(accA, m0, c0, m1, c1, sb, 2 * i, 0, 0);
          TR(48 + 2 * i);
          stage(IC<6>{}, IC<2>{}, true);
          stage_tile<2, 4>(accA, m0, c0, m1, c1, sb, 2 * i, 0, 0);
          stage(IC<7>{}, IC<2>{}, true);
          stage_done(sb, 2 * i, 1);
          if (i == 3 && (tid_now() & 31) == 0) mbar_arrive(sb + B_XF);
          stage(IC<8>{}, IC<2>{}, true);
          stage(IC<0>{}, IC<2>{}, true);
          if (i == 3) mbar_wait(sb + B_XF, L);
          stage_tile<0, 2>(accB, m0, c0, m1, c1, sb, 2 * i + 1, 0, 0);
          TR(49 + 2 * i);
        }
        stage(IC<1>{}, IC<2>{}, true);
        stage_tile<2, 4>(accB, m0, c0, m1, c1, sb, 7, 7, DN_LATE ? 0 : 1);
        stage(IC<2>{}, IC<2>{}, true);
        if (DN_LATE) stage_done(sb, 7, 1);
        stage(IC<3>{}, IC<2>{}, true);
        stage(IC<4>{}, IC<1>{}, true);
        wgmma_wait<0>();
        release_slot(sb, 1);
        stage_tile(accA, m0, c0, m1, c1, sb, 8, 8, 1);
        TR(56);
        TS(12);
      }
    }
  }
}

__global__ void probe_kernel() {}

typedef CUresult (*PFN_tmEncode)(CUtensorMap*, CUtensorMapDataType, cuuint32_t, void*, const cuuint64_t*,
                                 const cuuint64_t*, const cuuint32_t*, const cuuint32_t*, CUtensorMapInterleave,
                                 CUtensorMapSwizzle, CUtensorMapL2promotion, CUtensorMapFloatOOBfill);

static void encode_2d(PFN_tmEncode fn, CUtensorMap* m, const void* ptr, uint64_t inner, uint64_t outer, uint32_t box_inner,
                      uint32_t box_outer) {
  cuuint64_t dims[2] = {inner, outer};
  cuuint64_t strides[1] = {inner * 2};
  cuuint32_t box[2] = {box_inner, box_outer};
  cuuint32_t estr[2] = {1, 1};
  fn(m, CU_TENSOR_MAP_DATA_TYPE_BFLOAT16, 2, const_cast<void*>(ptr), dims, strides, box, estr,
     CU_TENSOR_MAP_INTERLEAVE_NONE, CU_TENSOR_MAP_SWIZZLE_128B, CU_TENSOR_MAP_L2_PROMOTION_L2_256B,
     CU_TENSOR_MAP_FLOAT_OOB_FILL_NONE);
}

static void encode_3d(PFN_tmEncode fn, CUtensorMap* m, const void* ptr, uint64_t d0, uint64_t d1, uint64_t d2, uint64_t s1,
                      uint64_t s2, uint32_t b0, uint32_t b1, uint32_t b2, CUtensorMapL2promotion prom) {
  cuuint64_t dims[3] = {d0, d1, d2};
  cuuint64_t strides[2] = {s1, s2};
  cuuint32_t box[3] = {b0, b1, b2};
  cuuint32_t estr[3] = {1, 1, 1};
  fn(m, CU_TENSOR_MAP_DATA_TYPE_BFLOAT16, 3, const_cast<void*>(ptr), dims, strides, box, estr, CU_TENSOR_MAP_INTERLEAVE_NONE,
     CU_TENSOR_MAP_SWIZZLE_128B, prom, CU_TENSOR_MAP_FLOAT_OOB_FILL_NONE);
}

}

extern "C" void kernel_launch(void* const* d_in, const int* in_sizes, int n_in, void* d_out, int out_size) {
  const __nv_bfloat16* x0 = (const __nv_bfloat16*)d_in[0];
  const __nv_bfloat16* wqkv = (const __nv_bfloat16*)d_in[1];
  const __nv_bfloat16* wo = (const __nv_bfloat16*)d_in[2];
  const __nv_bfloat16* wg = (const __nv_bfloat16*)d_in[4];
  const __nv_bfloat16* wu = (const __nv_bfloat16*)d_in[5];
  const __nv_bfloat16* wd = (const __nv_bfloat16*)d_in[6];
  static PFN_tmEncode enc = nullptr;
  if (!enc) {
    void* fn = nullptr;
    cudaDriverEntryPointQueryResult qr;
    cudaGetDriverEntryPoint("cuTensorMapEncodeTiled", &fn, cudaEnableDefault, &qr);
    enc = (PFN_tmEncode)fn;
  }
  Maps mp;
  encode_3d(enc, &mp.x0, x0, DM, SEQ / 2, 2, DM * 4, DM * 2, 64, 32, 2, CU_TENSOR_MAP_L2_PROMOTION_L2_256B);
  encode_3d(enc, &mp.r, d_out, DM, SEQ / 2, 2, DM * 4, DM * 2, 64, 32, 2, CU_TENSOR_MAP_L2_PROMOTION_L2_256B);
  encode_3d(enc, &mp.wq, wqkv, 576, 576, 3, NQKV * 2, 576 * 2, 64, 16, 3, CU_TENSOR_MAP_L2_PROMOTION_L2_128B);
  encode_2d(enc, &mp.wo, wo, DM, DM, 64, 72);
  encode_2d(enc, &mp.wg, wg, FF, DM, 64, 64);
  encode_2d(enc, &mp.wu, wu, FF, DM, 64, 64);
  encode_2d(enc, &mp.wd, wd, DM, FF, 64, 64);
  cudaFuncSetAttribute(mega_kernel, cudaFuncAttributeMaxDynamicSharedMemorySize, SMEM_BYTES);
  static int small_gpc = -1;
  if (small_gpc < 0) {
    cudaFuncSetAttribute(probe_kernel, cudaFuncAttributeMaxDynamicSharedMemorySize, SMEM_BYTES);
    cudaFuncSetAttribute(probe_kernel, cudaFuncAttributeNonPortableClusterSizeAllowed, 1);
    int n[2] = {0, 0};
    for (int i = 0; i < 2; ++i) {
      cudaLaunchConfig_t cfg = {};
      cfg.gridDim = dim3(128);
      cfg.blockDim = dim3(384);
      cfg.dynamicSmemBytes = SMEM_BYTES;
      cudaLaunchAttribute at;
      at.id = cudaLaunchAttributeClusterDimension;
      at.val.clusterDim.x = 8 << i;
      at.val.clusterDim.y = at.val.clusterDim.z = 1;
      cfg.attrs = &at;
      cfg.numAttrs = 1;
      if (cudaOccupancyMaxActiveClusters(&n[i], probe_kernel, &cfg) != cudaSuccess) cudaGetLastError();
    }
    small_gpc = n[0] == 15 && n[1] == 7;
  }
  mega_kernel<<<128, 384, SMEM_BYTES, cudaStreamPerThread>>>(mp, x0, wqkv, wo, (__nv_bfloat16*)d_out, small_gpc);
}
```

```cpp
#include <cuda_runtime.h>
#include <cuda_bf16.h>
#include <cuda.h>
#include <stdint.h>

namespace {

constexpr int SEQ = 2048, DM = 576, FF = 4608, NQKV = 1728;

__device__ __align__(128) uint4 g_halo[128 * 384];
__device__ __align__(1024) uint4 g_wimg[8 * 18 * 1024];
__device__ __align__(128) uint4 g_stat[SEQ];
__device__ __align__(128) float g_csq[4 * NQKV];
__device__ __align__(128) float g_wsum[DM];
constexpr int FL_J = 64 * 32, FL_W = FL_J + 32;
__device__ __align__(128) unsigned int g_flag[FL_W + 32];
__device__ unsigned int g_epoch[128];
__device__ unsigned int g_claim[8];

__device__ __forceinline__ uint32_t smem_u32(const void* p) { return (uint32_t)__cvta_generic_to_shared(p); }
__device__ __forceinline__ void mbar_init(uint32_t bar, uint32_t count) {
  asm volatile("mbarrier.init.shared::cta.b64 [%0], %1;" ::"r"(bar), "r"(count) : "memory");
}
__device__ __forceinline__ void mbar_expect_tx(uint32_t bar, uint32_t bytes) {
  asm volatile("mbarrier.arrive.expect_tx.shared::cta.b64 _, [%0], %1;" ::"r"(bar), "r"(bytes) : "memory");
}
__device__ __forceinline__ void mbar_arrive(uint32_t bar) {
  asm volatile("mbarrier.arrive.shared::cta.b64 _, [%0];" ::"r"(bar) : "memory");
}
#define SPIN_LIMIT "1048576"
#define SPIN_MAX 1048576
__device__ __forceinline__ void mbar_wait(uint32_t bar, uint32_t parity) {
  asm volatile(
      "{\n.reg .pred p, c;\n.reg .u32 n;\nmov.u32 n, 0;\n"
      "WAIT:\nmbarrier.try_wait.parity.shared::cta.b64 p, [%0], %1;\n"
      "add.u32 n, n, 1;\nsetp.lt.and.u32 c, n, " SPIN_LIMIT ", !p;\n@c bra.uni WAIT;\n}"
      :
      : "r"(bar), "r"(parity)
      : "memory");
}
__device__ __forceinline__ void mbar_wait2(uint32_t a, uint32_t pa, uint32_t b, uint32_t pb) {
  asm volatile(
      "{\n.reg .pred p, q, c;\n.reg .u32 n;\nmov.u32 n, 0;\n"
      "WAIT:\nmbarrier.try_wait.parity.shared::cta.b64 p, [%0], %1;\nmbarrier.try_wait.parity.shared::cta.b64 q, [%2], %3;\n"
      "add.u32 n, n, 1;\nand.pred p, p, q;\nsetp.lt.and.u32 c, n, " SPIN_LIMIT ", !p;\n@c bra.uni WAIT;\n}"
      :
      : "r"(a), "r"(pa), "r"(b), "r"(pb)
      : "memory");
}
__device__ __forceinline__ void mbar_wait3(uint32_t a, uint32_t pa, uint32_t b, uint32_t pb, uint32_t d, uint32_t pd) {
  asm volatile(
      "{\n.reg .pred p, q, r, c;\n.reg .u32 n;\nmov.u32 n, 0;\n"
      "WAIT:\nmbarrier.try_wait.parity.shared::cta.b64 p, [%0], %1;\nmbarrier.try_wait.parity.shared::cta.b64 q, [%2], %3;\n"
      "mbarrier.try_wait.parity.shared::cta.b64 r, [%4], %5;\n"
      "add.u32 n, n, 1;\nand.pred p, p, q;\nand.pred p, p, r;\nsetp.lt.and.u32 c, n, " SPIN_LIMIT ", !p;\n@c bra.uni WAIT;\n}"
      :
      : "r"(a), "r"(pa), "r"(b), "r"(pb), "r"(d), "r"(pd)
      : "memory");
}
__device__ __forceinline__ void mbar_arrive_if(uint32_t bar, bool on) {
  asm volatile("{\n.reg .pred p;\nsetp.ne.u32 p, %1, 0;\n@p mbarrier.arrive.shared::cluster.b64 _, [%0];\n}" ::"r"(bar), "r"((uint32_t)on) : "memory");
}
__device__ __forceinline__ bool mbar_test(uint32_t bar, uint32_t parity) {
  uint32_t r;
  asm volatile("{\n.reg .pred p;\nmbarrier.test_wait.parity.shared::cta.b64 p, [%1], %2;\nselp.u32 %0, 1, 0, p;\n}"
               : "=r"(r) : "r"(bar), "r"(parity) : "memory");
  return r != 0;
}
__device__ __forceinline__ void poll_ge(const unsigned int* p, unsigned int target) {
  asm volatile(
      "{\n.reg .pred p, c;\n.reg .u32 n;\n.reg .s32 v;\nmov.u32 n, 0;\n"
      "POLL:\nld.relaxed.gpu.global.u32 v, [%0];\nsub.s32 v, v, %1;\nsetp.lt.s32 p, v, 0;\n"
      "add.u32 n, n, 1;\nsetp.lt.and.u32 c, n, " SPIN_LIMIT ", p;\n@c bra.uni POLL;\n}"
      :
      : "l"(p), "r"(target)
      : "memory");
}
__device__ __forceinline__ void signal_release(unsigned int* p, uint32_t v = 1) {
  asm volatile("red.release.gpu.global.add.u32 [%0], %1;" ::"l"(p), "r"(v) : "memory");
}
__device__ __forceinline__ void signal_relaxed(unsigned int* p, uint32_t v = 1) {
  asm volatile("red.relaxed.gpu.global.add.u32 [%0], %1;" ::"l"(p), "r"(v) : "memory");
}
__device__ __forceinline__ bool elect_one() {
  uint32_t pred;
  asm volatile("{\n.reg .pred p;\nelect.sync _|p, 0xffffffff;\nselp.u32 %0, 1, 0, p;\n}" : "=r"(pred));
  return pred != 0;
}
__device__ __forceinline__ void tma_load_2d(uint32_t dst, const CUtensorMap* map, uint32_t bar, int c0, int c1) {
  asm volatile(
      "cp.async.bulk.tensor.2d.shared::cluster.global.mbarrier::complete_tx::bytes [%0], [%1, {%3, %4}], [%2];" ::"r"(dst),
      "l"(map), "r"(bar), "r"(c0), "r"(c1)
      : "memory");
}
__device__ __forceinline__ void tma_load_3d(uint32_t dst, const CUtensorMap* map, uint32_t bar, int c0, int c1, int c2) {
  asm volatile(
      "cp.async.bulk.tensor.3d.shared::cluster.global.mbarrier::complete_tx::bytes [%0], [%1, {%3, %4, %5}], [%2];" ::"r"(dst),
      "l"(map), "r"(bar), "r"(c0), "r"(c1), "r"(c2)
      : "memory");
}
__device__ __forceinline__ void tma_load_3d_mc(uint32_t dst, const CUtensorMap* map, uint32_t bar, int c0, int c1, int c2) {
  asm volatile(
      "cp.async.bulk.tensor.3d.shared::cluster.global.mbarrier::complete_tx::bytes.multicast::cluster [%0], [%1, {%3, "
      "%4, %5}], [%2], %6;" ::"r"(dst),
      "l"(map), "r"(bar), "r"(c0), "r"(c1), "r"(c2), "h"((uint16_t)3)
      : "memory");
}
__device__ __forceinline__ void st_async_u4(uint32_t dst, uint32_t bar, uint32_t a, uint32_t b, uint32_t c, uint32_t d) {
  asm volatile("st.async.weak.shared::cluster.mbarrier::complete_tx::bytes.v4.b32 [%0], {%2, %3, %4, %5}, [%1];" ::"r"(dst),
               "r"(bar), "r"(a), "r"(b), "r"(c), "r"(d)
               : "memory");
}
__device__ __forceinline__ void tma_reduce_3d(const CUtensorMap* map, uint32_t src, int c0, int c1, int c2) {
  asm volatile("cp.reduce.async.bulk.tensor.3d.global.shared::cta.add.tile.bulk_group [%0, {%2, %3, %4}], [%1];" ::"l"(map),
               "r"(src), "r"(c0), "r"(c1), "r"(c2)
               : "memory");
}
__device__ __forceinline__ void tma_store_3d(const CUtensorMap* map, uint32_t src, int c0, int c1, int c2) {
  asm volatile("cp.async.bulk.tensor.3d.global.shared::cta.tile.bulk_group [%0, {%2, %3, %4}], [%1];" ::"l"(map), "r"(src),
               "r"(c0), "r"(c1), "r"(c2)
               : "memory");
}
__device__ __forceinline__ void tma_prefetch_2d(const CUtensorMap* map, int c0, int c1) {
  asm volatile("cp.async.bulk.prefetch.tensor.2d.L2.global.tile [%0, {%1, %2}];" ::"l"(map), "r"(c0), "r"(c1) : "memory");
}
__device__ __forceinline__ void prefetch_map(const CUtensorMap* map) {
  asm volatile("prefetch.tensormap [%0];" ::"l"(map) : "memory");
}
__device__ __forceinline__ void wgmma_fence() { asm volatile("wgmma.fence.sync.aligned;" ::: "memory"); }
__device__ __forceinline__ void wgmma_commit() { asm volatile("wgmma.commit_group.sync.aligned;" ::: "memory"); }
template <int N>
__device__ __forceinline__ void wgmma_wait() {
  asm volatile("wgmma.wait_group.sync.aligned %0;" ::"n"(N) : "memory");
}
__device__ __forceinline__ void named_bar_sync(int id, int nthreads) {
  asm volatile("bar.sync %0, %1;" ::"r"(id), "r"(nthreads) : "memory");
}
__device__ __forceinline__ void cluster_arrive_relaxed() { asm volatile("barrier.cluster.arrive.relaxed.aligned;" ::: "memory"); }
__device__ __forceinline__ void cluster_wait() { asm volatile("barrier.cluster.wait.acquire.aligned;" ::: "memory"); }
__device__ __forceinline__ uint32_t mapa(uint32_t addr, uint32_t rank) {
  uint32_t r;
  asm volatile("mapa.shared::cluster.u32 %0, %1, %2;" : "=r"(r) : "r"(addr), "r"(rank));
  return r;
}
__device__ __forceinline__ uint64_t desc_from_lo(uint32_t lo) { return (uint64_t)lo | (0x40000040ull << 32); }
__device__ __forceinline__ uint64_t desc_sbo(uint32_t lo, uint32_t sbo) { return (uint64_t)lo | ((0x40000000ull | (sbo >> 4)) << 32); }
__device__ __forceinline__ uint32_t desc_lo_a(uint32_t addr) { return ((addr & 0x3FFFF) >> 4) | (1u << 16); }
__device__ __forceinline__ uint32_t desc_lo_b(uint32_t addr, uint32_t lbo_bytes) { return ((addr & 0x3FFFF) >> 4) | ((lbo_bytes >> 4) << 16); }
__device__ __forceinline__ uint32_t pack_bf16(float lo, float hi) {
  __nv_bfloat162 v = __floats2bfloat162_rn(lo, hi);
  return *reinterpret_cast<uint32_t*>(&v);
}
__device__ __forceinline__ float bf16r(float x) { return __uint_as_float(pack_bf16(0.f, x)); }
__device__ __forceinline__ float bf_lo(uint32_t u) { return __uint_as_float(u << 16); }
__device__ __forceinline__ float bf_hi(uint32_t u) { return __uint_as_float(u & 0xFFFF0000u); }
__device__ __forceinline__ uint4 lds_u4(uint32_t addr) {
  uint4 v;
  asm volatile("ld.shared.v4.b32 {%0, %1, %2, %3}, [%4];" : "=r"(v.x), "=r"(v.y), "=r"(v.z), "=r"(v.w) : "r"(addr) : "memory");
  return v;
}
__device__ __forceinline__ float2 lds_f2(uint32_t addr) {
  float2 v;
  asm volatile("ld.shared.v2.f32 {%0, %1}, [%2];" : "=f"(v.x), "=f"(v.y) : "r"(addr) : "memory");
  return v;
}
__device__ __forceinline__ void sts_f2(uint32_t addr, float a, float b) {
  asm volatile("st.shared.v2.f32 [%0], {%1, %2};" ::"r"(addr), "f"(a), "f"(b) : "memory");
}
__device__ __forceinline__ void sts_u4(uint32_t addr, uint32_t a, uint32_t b, uint32_t c, uint32_t d) {
  asm volatile("st.shared.v4.b32 [%0], {%1, %2, %3, %4};" ::"r"(addr), "r"(a), "r"(b), "r"(c), "r"(d) : "memory");
}
__device__ __forceinline__ void sts_u32(uint32_t addr, uint32_t v) { asm volatile("st.shared.b32 [%0], %1;" ::"r"(addr), "r"(v) : "memory"); }
__device__ __forceinline__ uint32_t lds_u32(uint32_t addr) {
  uint32_t v;
  asm volatile("ld.shared.b32 %0, [%1];" : "=r"(v) : "r"(addr) : "memory");
  return v;
}
__device__ __forceinline__ uint4 ldg_u4(const void* p, bool on = true) {
  uint4 v = make_uint4(0u, 0u, 0u, 0u);
  asm volatile("{\n.reg .pred p;\nsetp.ne.u32 p, %5, 0;\n@p ld.global.nc.L1::no_allocate.v4.b32 {%0, %1, %2, %3}, [%4];\n}"
               : "+r"(v.x), "+r"(v.y), "+r"(v.z), "+r"(v.w) : "l"(p), "r"((uint32_t)on) : "memory");
  return v;
}
__device__ __forceinline__ float4 ldg_cg_f4(const void* p) {
  float4 v;
  asm volatile("ld.global.cg.v4.f32 {%0, %1, %2, %3}, [%4];" : "=f"(v.x), "=f"(v.y), "=f"(v.z), "=f"(v.w) : "l"(p) : "memory");
  return v;
}
__device__ __forceinline__ void st_tagged(void* p, uint32_t a, uint32_t b, uint32_t c, uint32_t tag) {
  asm volatile("{\n.reg .b64 l, h;\n.reg .b128 v;\nmov.b64 l, {%1, %2};\nmov.b64 h, {%3, %4};\nmov.b128 v, {l, h};\n"
               "st.relaxed.gpu.global.b128 [%0], v;\n}" ::"l"(p), "r"(a), "r"(b), "r"(c), "r"(tag) : "memory");
}
__device__ __forceinline__ void st_tagged_any(uint64_t p, uint32_t a, uint32_t b, uint32_t c, uint32_t tag) {
  asm volatile("{\n.reg .b64 l, h;\n.reg .b128 v;\nmov.b64 l, {%1, %2};\nmov.b64 h, {%3, %4};\nmov.b128 v, {l, h};\n"
               "st.relaxed.gpu.b128 [%0], v;\n}" ::"l"(p), "r"(a), "r"(b), "r"(c), "r"(tag) : "memory");
}
__device__ __forceinline__ uint4 ld_tagged(const void* p) {
  uint4 r;
  asm volatile("{\n.reg .b64 l, h;\n.reg .b128 v;\nld.relaxed.gpu.global.b128 v, [%4];\nmov.b128 {l, h}, v;\n"
               "mov.b64 {%0, %1}, l;\nmov.b64 {%2, %3}, h;\n}" : "=r"(r.x), "=r"(r.y), "=r"(r.z), "=r"(r.w) : "l"(p) : "memory");
  return r;
}
__device__ __forceinline__ void cp_async16(uint32_t dst, const void* src) {
  asm volatile("cp.async.cg.shared.global [%0], [%1], 16;" ::"r"(dst), "l"(src) : "memory");
}
__device__ __forceinline__ void cp_async_arrive(uint32_t bar) {
  asm volatile("cp.async.mbarrier.arrive.shared::cta.b64 [%0];" ::"r"(bar) : "memory");
}
__device__ __forceinline__ void bulk_store(void* gdst, uint32_t src, uint32_t bytes) {
  asm volatile("cp.async.bulk.global.shared::cta.bulk_group [%0], [%1], %2;" ::"l"(gdst), "r"(src), "r"(bytes) : "memory");
}
__device__ __forceinline__ void bulk_load(uint32_t dst, const void* gsrc, uint32_t bytes, uint32_t bar) {
  asm volatile("cp.async.bulk.shared::cluster.global.mbarrier::complete_tx::bytes [%0], [%1], %2, [%3];" ::"r"(dst), "l"(gsrc),
               "r"(bytes), "r"(bar)
               : "memory");
}
__device__ __forceinline__ void bulk_commit() { asm volatile("cp.async.bulk.commit_group;" ::: "memory"); }
template <int N>
__device__ __forceinline__ void bulk_wait() { asm volatile("cp.async.bulk.wait_group %0;" ::"n"(N) : "memory"); }
__device__ __forceinline__ void stsm_x4(uint32_t addr, uint32_t a, uint32_t b, uint32_t c, uint32_t d) {
  asm volatile("stmatrix.sync.aligned.m8n8.x4.shared.b16 [%0], {%1, %2, %3, %4};" ::"r"(addr), "r"(a), "r"(b), "r"(c), "r"(d) : "memory");
}
__device__ __forceinline__ uint32_t movm(uint32_t a) {
  uint32_t d;
  asm volatile("movmatrix.sync.aligned.m8n8.trans.b16 %0, %1;" : "=r"(d) : "r"(a));
  return d;
}
__device__ __forceinline__ void mma_16816(float (&d)[4], uint32_t a0, uint32_t a1, uint32_t a2, uint32_t a3, uint32_t b0, uint32_t b1) {
  asm volatile("mma.sync.aligned.m16n8k16.row.col.f32.bf16.bf16.f32 {%0, %1, %2, %3}, {%4, %5, %6, %7}, {%8, %9}, {%0, %1, %2, %3};"
               : "+f"(d[0]), "+f"(d[1]), "+f"(d[2]), "+f"(d[3]) : "r"(a0), "r"(a1), "r"(a2), "r"(a3), "r"(b0), "r"(b1));
}
__device__ __forceinline__ void mma_16816_z(float (&d)[4], uint32_t a0, uint32_t a1, uint32_t a2, uint32_t a3, uint32_t b0, uint32_t b1) {
  asm volatile("mma.sync.aligned.m16n8k16.row.col.f32.bf16.bf16.f32 {%0, %1, %2, %3}, {%4, %5, %6, %7}, {%8, %9}, {%10, %10, %10, %10};"
               : "=f"(d[0]), "=f"(d[1]), "=f"(d[2]), "=f"(d[3]) : "r"(a0), "r"(a1), "r"(a2), "r"(a3), "r"(b0), "r"(b1), "f"(0.f));
}
__device__ __forceinline__ void mma_1688(float (&d)[4], uint32_t a0, uint32_t a1, uint32_t b0) {
  asm volatile("mma.sync.aligned.m16n8k8.row.col.f32.bf16.bf16.f32 {%0, %1, %2, %3}, {%4, %5}, {%6}, {%7, %7, %7, %7};"
               : "=f"(d[0]), "=f"(d[1]), "=f"(d[2]), "=f"(d[3]) : "r"(a0), "r"(a1), "r"(b0), "f"(0.f));
}
__device__ __forceinline__ void fence_proxy_async() { asm volatile("fence.proxy.async.shared::cta;" ::: "memory"); }

template<int N> __device__ __forceinline__ void wgmma_ss(float (&d)[N/2], uint64_t descA, uint64_t descB, int scaleD);
template<int N> __device__ __forceinline__ void wgmma_rs(float (&d)[N/2], uint32_t a0, uint32_t a1, uint32_t a2, uint32_t a3, uint64_t descB, int scaleD);
template<> __device__ __forceinline__ void wgmma_ss<128>(float (&d)[64], uint64_t descA, uint64_t descB, int scaleD) {
  asm volatile("{\n.reg .pred p;\nsetp.ne.b32 p, %66, 0;\n"
    "wgmma.mma_async.sync.aligned.m64n128k16.f32.bf16.bf16 {%0, %1, %2, %3, %4, %5, %6, %7, %8, %9, %10, %11, %12, %13, %14, %15, %16, %17, %18, %19, %20, %21, %22, %23, %24, %25, %26, %27, %28, %29, %30, %31, %32, %33, %34, %35, %36, %37, %38, %39, %40, %41, %42, %43, %44, %45, %46, %47, %48, %49, %50, %51, %52, %53, %54, %55, %56, %57, %58, %59, %60, %61, %62, %63}, %64, %65, p, 1, 1, 0, 1;\n}\n"
    : "+f"(d[0]), "+f"(d[1]), "+f"(d[2]), "+f"(d[3]), "+f"(d[4]), "+f"(d[5]), "+f"(d[6]), "+f"(d[7]), "+f"(d[8]), "+f"(d[9]), "+f"(d[10]), "+f"(d[11]), "+f"(d[12]), "+f"(d[13]), "+f"(d[14]), "+f"(d[15]), "+f"(d[16]), "+f"(d[17]), "+f"(d[18]), "+f"(d[19]), "+f"(d[20]), "+f"(d[21]), "+f"(d[22]), "+f"(d[23]), "+f"(d[24]), "+f"(d[25]), "+f"(d[26]), "+f"(d[27]), "+f"(d[28]), "+f"(d[29]), "+f"(d[30]), "+f"(d[31]), "+f"(d[32]), "+f"(d[33]), "+f"(d[34]), "+f"(d[35]), "+f"(d[36]), "+f"(d[37]), "+f"(d[38]), "+f"(d[39]), "+f"(d[40]), "+f"(d[41]), "+f"(d[42]), "+f"(d[43]), "+f"(d[44]), "+f"(d[45]), "+f"(d[46]), "+f"(d[47]), "+f"(d[48]), "+f"(d[49]), "+f"(d[50]), "+f"(d[51]), "+f"(d[52]), "+f"(d[53]), "+f"(d[54]), "+f"(d[55]), "+f"(d[56]), "+f"(d[57]), "+f"(d[58]), "+f"(d[59]), "+f"(d[60]), "+f"(d[61]), "+f"(d[62]), "+f"(d[63])
    : "l"(descA), "l"(descB), "r"(scaleD));
}
template<> __device__ __forceinline__ void wgmma_ss<216>(float (&d)[108], uint64_t descA, uint64_t descB, int scaleD) {
  asm volatile("{\n.reg .pred p;\nsetp.ne.b32 p, %110, 0;\n"
    "wgmma.mma_async.sync.aligned.m64n216k16.f32.bf16.bf16 {%0, %1, %2, %3, %4, %5, %6, %7, %8, %9, %10, %11, %12, %13, %14, %15, %16, %17, %18, %19, %20, %21, %22, %23, %24, %25, %26, %27, %28, %29, %30, %31, %32, %33, %34, %35, %36, %37, %38, %39, %40, %41, %42, %43, %44, %45, %46, %47, %48, %49, %50, %51, %52, %53, %54, %55, %56, %57, %58, %59, %60, %61, %62, %63, %64, %65, %66, %67, %68, %69, %70, %71, %72, %73, %74, %75, %76, %77, %78, %79, %80, %81, %82, %83, %84, %85, %86, %87, %88, %89, %90, %91, %92, %93, %94, %95, %96, %97, %98, %99, %100, %101, %102, %103, %104, %105, %106, %107}, %108, %109, p, 1, 1, 0, 1;\n}\n"
    : "+f"(d[0]), "+f"(d[1]), "+f"(d[2]), "+f"(d[3]), "+f"(d[4]), "+f"(d[5]), "+f"(d[6]), "+f"(d[7]), "+f"(d[8]), "+f"(d[9]), "+f"(d[10]), "+f"(d[11]), "+f"(d[12]), "+f"(d[13]), "+f"(d[14]), "+f"(d[15]), "+f"(d[16]), "+f"(d[17]), "+f"(d[18]), "+f"(d[19]), "+f"(d[20]), "+f"(d[21]), "+f"(d[22]), "+f"(d[23]), "+f"(d[24]), "+f"(d[25]), "+f"(d[26]), "+f"(d[27]), "+f"(d[28]), "+f"(d[29]), "+f"(d[30]), "+f"(d[31]), "+f"(d[32]), "+f"(d[33]), "+f"(d[34]), "+f"(d[35]), "+f"(d[36]), "+f"(d[37]), "+f"(d[38]), "+f"(d[39]), "+f"(d[40]), "+f"(d[41]), "+f"(d[42]), "+f"(d[43]), "+f"(d[44]), "+f"(d[45]), "+f"(d[46]), "+f"(d[47]), "+f"(d[48]), "+f"(d[49]), "+f"(d[50]), "+f"(d[51]), "+f"(d[52]), "+f"(d[53]), "+f"(d[54]), "+f"(d[55]), "+f"(d[56]), "+f"(d[57]), "+f"(d[58]), "+f"(d[59]), "+f"(d[60]), "+f"(d[61]), "+f"(d[62]), "+f"(d[63]), "+f"(d[64]), "+f"(d[65]), "+f"(d[66]), "+f"(d[67]), "+f"(d[68]), "+f"(d[69]), "+f"(d[70]), "+f"(d[71]), "+f"(d[72]), "+f"(d[73]), "+f"(d[74]), "+f"(d[75]), "+f"(d[76]), "+f"(d[77]), "+f"(d[78]), "+f"(d[79]), "+f"(d[80]), "+f"(d[81]), "+f"(d[82]), "+f"(d[83]), "+f"(d[84]), "+f"(d[85]), "+f"(d[86]), "+f"(d[87]), "+f"(d[88]), "+f"(d[89]), "+f"(d[90]), "+f"(d[91]), "+f"(d[92]), "+f"(d[93]), "+f"(d[94]), "+f"(d[95]), "+f"(d[96]), "+f"(d[97]), "+f"(d[98]), "+f"(d[99]), "+f"(d[100]), "+f"(d[101]), "+f"(d[102]), "+f"(d[103]), "+f"(d[104]), "+f"(d[105]), "+f"(d[106]), "+f"(d[107])
    : "l"(descA), "l"(descB), "r"(scaleD));
}
template<> __device__ __forceinline__ void wgmma_rs<64>(float (&d)[32], uint32_t a0, uint32_t a1, uint32_t a2, uint32_t a3, uint64_t descB, int scaleD) {
  asm volatile("{\n.reg .pred p;\nsetp.ne.b32 p, %37, 0;\n"
    "wgmma.mma_async.sync.aligned.m64n64k16.f32.bf16.bf16 {%0, %1, %2, %3, %4, %5, %6, %7, %8, %9, %10, %11, %12, %13, %14, %15, %16, %17, %18, %19, %20, %21, %22, %23, %24, %25, %26, %27, %28, %29, %30, %31}, {%32, %33, %34, %35}, %36, p, 1, 1, 1;\n}\n"
    : "+f"(d[0]), "+f"(d[1]), "+f"(d[2]), "+f"(d[3]), "+f"(d[4]), "+f"(d[5]), "+f"(d[6]), "+f"(d[7]), "+f"(d[8]), "+f"(d[9]), "+f"(d[10]), "+f"(d[11]), "+f"(d[12]), "+f"(d[13]), "+f"(d[14]), "+f"(d[15]), "+f"(d[16]), "+f"(d[17]), "+f"(d[18]), "+f"(d[19]), "+f"(d[20]), "+f"(d[21]), "+f"(d[22]), "+f"(d[23]), "+f"(d[24]), "+f"(d[25]), "+f"(d[26]), "+f"(d[27]), "+f"(d[28]), "+f"(d[29]), "+f"(d[30]), "+f"(d[31])
    : "r"(a0), "r"(a1), "r"(a2), "r"(a3), "l"(descB), "r"(scaleD));
}
template<> __device__ __forceinline__ void wgmma_rs<216>(float (&d)[108], uint32_t a0, uint32_t a1, uint32_t a2, uint32_t a3, uint64_t descB, int scaleD) {
  asm volatile("{\n.reg .pred p;\nsetp.ne.b32 p, %113, 0;\n"
    "wgmma.mma_async.sync.aligned.m64n216k16.f32.bf16.bf16 {%0, %1, %2, %3, %4, %5, %6, %7, %8, %9, %10, %11, %12, %13, %14, %15, %16, %17, %18, %19, %20, %21, %22, %23, %24, %25, %26, %27, %28, %29, %30, %31, %32, %33, %34, %35, %36, %37, %38, %39, %40, %41, %42, %43, %44, %45, %46, %47, %48, %49, %50, %51, %52, %53, %54, %55, %56, %57, %58, %59, %60, %61, %62, %63, %64, %65, %66, %67, %68, %69, %70, %71, %72, %73, %74, %75, %76, %77, %78, %79, %80, %81, %82, %83, %84, %85, %86, %87, %88, %89, %90, %91, %92, %93, %94, %95, %96, %97, %98, %99, %100, %101, %102, %103, %104, %105, %106, %107}, {%108, %109, %110, %111}, %112, p, 1, 1, 1;\n}\n"
    : "+f"(d[0]), "+f"(d[1]), "+f"(d[2]), "+f"(d[3]), "+f"(d[4]), "+f"(d[5]), "+f"(d[6]), "+f"(d[7]), "+f"(d[8]), "+f"(d[9]), "+f"(d[10]), "+f"(d[11]), "+f"(d[12]), "+f"(d[13]), "+f"(d[14]), "+f"(d[15]), "+f"(d[16]), "+f"(d[17]), "+f"(d[18]), "+f"(d[19]), "+f"(d[20]), "+f"(d[21]), "+f"(d[22]), "+f"(d[23]), "+f"(d[24]), "+f"(d[25]), "+f"(d[26]), "+f"(d[27]), "+f"(d[28]), "+f"(d[29]), "+f"(d[30]), "+f"(d[31]), "+f"(d[32]), "+f"(d[33]), "+f"(d[34]), "+f"(d[35]), "+f"(d[36]), "+f"(d[37]), "+f"(d[38]), "+f"(d[39]), "+f"(d[40]), "+f"(d[41]), "+f"(d[42]), "+f"(d[43]), "+f"(d[44]), "+f"(d[45]), "+f"(d[46]), "+f"(d[47]), "+f"(d[48]), "+f"(d[49]), "+f"(d[50]), "+f"(d[51]), "+f"(d[52]), "+f"(d[53]), "+f"(d[54]), "+f"(d[55]), "+f"(d[56]), "+f"(d[57]), "+f"(d[58]), "+f"(d[59]), "+f"(d[60]), "+f"(d[61]), "+f"(d[62]), "+f"(d[63]), "+f"(d[64]), "+f"(d[65]), "+f"(d[66]), "+f"(d[67]), "+f"(d[68]), "+f"(d[69]), "+f"(d[70]), "+f"(d[71]), "+f"(d[72]), "+f"(d[73]), "+f"(d[74]), "+f"(d[75]), "+f"(d[76]), "+f"(d[77]), "+f"(d[78]), "+f"(d[79]), "+f"(d[80]), "+f"(d[81]), "+f"(d[82]), "+f"(d[83]), "+f"(d[84]), "+f"(d[85]), "+f"(d[86]), "+f"(d[87]), "+f"(d[88]), "+f"(d[89]), "+f"(d[90]), "+f"(d[91]), "+f"(d[92]), "+f"(d[93]), "+f"(d[94]), "+f"(d[95]), "+f"(d[96]), "+f"(d[97]), "+f"(d[98]), "+f"(d[99]), "+f"(d[100]), "+f"(d[101]), "+f"(d[102]), "+f"(d[103]), "+f"(d[104]), "+f"(d[105]), "+f"(d[106]), "+f"(d[107])
    : "r"(a0), "r"(a1), "r"(a2), "r"(a3), "l"(descB), "r"(scaleD));
}

constexpr int TILE = 8192, HALF = 9 * TILE;
constexpr int SLOT = 16384;
constexpr int RING = 2 * HALF;
constexpr int OVF = RING + 5 * SLOT;
constexpr int TAB = OVF + 1024;
constexpr int BARS = TAB + 1024;
constexpr int SMEM_BYTES = BARS + 1024;
constexpr int WOA = 9216;
constexpr int B_FULL = BARS, B_FX = BARS + 56, B_AUX = BARS + 200, B_NB = BARS + 208, B_ROLE = BARS + 272, B_S1 = BARS + 280,
              B_ST = BARS + 288, B_EMPTY = BARS + 432, B_J = BARS + 488, B_XF = BARS + 496,
              B_QK = BARS + 504, B_RX = BARS + 512, B_SR = BARS + 528, B_OX = BARS + 536, B_HP = BARS + 552;
constexpr int S_ROLE = BARS + 568, S_EP = BARS + 572, S_WS = BARS + 576;

template <int V>
struct IC {
  static constexpr int value = V;
};
struct Maps {
  CUtensorMap x0, r, wq, wo, wg, wu, wd;
};

#define TA0(i)
#define TA(i)
#define TS(i)
#define TR(i)

__device__ __forceinline__ int tid_now() {
  int t;
  asm volatile("mov.u32 %0, %%tid.x;" : "=r"(t));
  return t;
}
__device__ __forceinline__ float quad_sum(float v) {
  v += __shfl_xor_sync(0xffffffffu, v, 1);
  return v + __shfl_xor_sync(0xffffffffu, v, 2);
}
__device__ __forceinline__ float inv_sd(float var) {
  float s, r;
  asm("sqrt.approx.ftz.f32 %0, %1;" : "=f"(s) : "f"(bf16r(bf16r(fmaxf(var, 0.f)) + 1e-5f)));
  asm("rcp.approx.ftz.f32 %0, %1;" : "=f"(r) : "f"(bf16r(s)));
  return r;
}
__device__ __forceinline__ float sum8(const uint4& v) {
  return ((bf_lo(v.x) + bf_hi(v.x)) + (bf_lo(v.y) + bf_hi(v.y))) + ((bf_lo(v.z) + bf_hi(v.z)) + (bf_lo(v.w) + bf_hi(v.w)));
}
__device__ __forceinline__ void warp_arrive(uint32_t bar) {
  __syncwarp();
  if ((tid_now() & 31) == 0) mbar_arrive(bar);
}
__device__ __forceinline__ void release_slot(uint32_t sb, int p, bool on = true) {
  asm volatile("{\n.reg .pred p;\nsetp.eq.u32 p, %1, 0;\n@p mbarrier.arrive.shared::cta.b64 _, [%0];\n}" ::"r"(sb + B_EMPTY + 8 * p),
               "r"((tid_now() & 31) | (on ? 0 : 1))
               : "memory");
}
__device__ __forceinline__ uint32_t stage_addr(uint32_t sb) {
  const int tid = tid_now(), lane = tid & 31;
  return sb + (tid >> 7) * HALF + ((tid >> 5) & 3) * 2048 + (lane & 15) * 128 + (((lane >> 4) ^ (lane & 7)) << 4);
}
__device__ __forceinline__ void stage_done(uint32_t sb, int a, int n) {
    __syncwarp();
  const int tid = tid_now();
  if ((tid & 31) < n) mbar_arrive(sb + B_ST + 72 * (tid >> 7) + 8 * (a + (tid & 31)));
}
template <int I0 = 0, int I1 = 4>
__device__ __forceinline__ void stage_tile(const float (&acc)[32], float m0, float c0, float m1, float c1, uint32_t sb, int a, int b, int n) {
  const uint32_t ad = stage_addr(sb) + a * TILE;
#pragma unroll
  for (int i = I0; i < I1; ++i)
    stsm_x4(ad ^ (i << 5), pack_bf16(fmaf(acc[8 * i], m0, c0), fmaf(acc[8 * i + 1], m0, c0)),
            pack_bf16(fmaf(acc[8 * i + 2], m1, c1), fmaf(acc[8 * i + 3], m1, c1)),
            pack_bf16(fmaf(acc[8 * i + 4], m0, c0), fmaf(acc[8 * i + 5], m0, c0)),
            pack_bf16(fmaf(acc[8 * i + 6], m1, c1), fmaf(acc[8 * i + 7], m1, c1)));
  if (n) stage_done(sb, b, n);
}

#define NLAYERS 2
#define X_EARLY 2
#define X_SCHED 0x1111111ull
#define PACE 2800
#define X_PF 0
#define DN_LATE 0
#define ST_END 5
#define GU_PF0 16
#define GU_PFN 16
#define R0_N 0
#define R1_N 2
#define PACE_R 1400
#define PACE0 4200
#define IMG 1
#define GU_PRE 1
#define Q_H 8
#define LAZY 2
#define Q_ST0 7
#define Q_ST1 6

__global__ void __cluster_dims__(2, 1, 1) __launch_bounds__(384, 1)
mega_kernel(const __grid_constant__ Maps mp, const __nv_bfloat16* __restrict__ x0, const __nv_bfloat16* __restrict__ wqkv,
            const __nv_bfloat16* __restrict__ wo, __nv_bfloat16* __restrict__ out, int small_gpc) {
  extern __shared__ __align__(1024) uint8_t smem[];
  const uint32_t sb = smem_u32(smem);
  const uint32_t rank = blockIdx.x & 1;
  const int warp = __shfl_sync(0xffffffffu, threadIdx.x >> 5, 0);
  TA0(63);
  uint32_t claim = 0, ep1 = 0;
  if (warp == 8) {
    if (threadIdx.x == 256 && rank == 0) {
      uint32_t tp;
      asm volatile("mov.u32 %0, %%smid;" : "=r"(tp));
      tp >>= 1;
      uint32_t pr = !small_gpc || tp < 32 ? tp & 7 : tp < 60 ? 1 + (tp - 32) % 7 : 0;
#pragma unroll 1
      for (int i = 0; i < 8; ++i, pr = (pr + 1) & 7) {
        claim = atomicAdd(&g_claim[pr], 1u);
        if (claim < 8) break;
      }
      claim = ((pr >> 2) * 8 + (claim & 7)) * 4 + (pr & 3);
    }
  } else {
    if (warp > 8) ep1 = g_epoch[blockIdx.x] + 1;
    if (elect_one()) {
      const uint32_t b0 = sb + BARS + 48 * (warp - (warp > 8));
      if (warp < 11) {
#pragma unroll
        for (int i = 0; i < 6; ++i) mbar_init(b0 + 8 * i, warp < 6 ? 1 : warp < 10 ? 4 : 8);
        if (warp == 5) mbar_expect_tx(sb + B_ROLE, 4);
      } else {
#pragma unroll
        for (int i = 0; i < 11; ++i) mbar_init(b0 + 8 * i, i < 3 ? 8 : i < 6 ? 4 : i < 7 ? 2 : 1);
      }
      asm volatile("fence.mbarrier_init.release.cluster;" ::: "memory");
      if (warp == 9) prefetch_map(&mp.x0);
      if (warp == 10) prefetch_map(&mp.wq);
    }
  }
  __syncwarp();
  cluster_arrive_relaxed();
  TA0(2);

  if (warp >= 8) {
    cluster_wait();
    if (threadIdx.x == 256 && rank == 0) {
#pragma unroll
      for (int r = 0; r < 2; ++r)
        asm volatile("st.async.weak.shared::cluster.mbarrier::complete_tx::bytes.u32 [%0], %1, [%2];" ::"r"(mapa(sb + S_ROLE, r)),
                     "r"(claim), "r"(mapa(sb + B_ROLE, r))
                     : "memory");
    }
    __syncwarp();
    asm volatile("setmaxnreg.dec.sync.aligned.u32 24;");
    mbar_wait(sb + B_ROLE, 0);
    const int role = __shfl_sync(0xffffffffu, lds_u32(sb + S_ROLE), 0);
    const int j = (role & 3) * 2 + rank, rb = role >> 2;
    ep1 = __shfl_sync(0xffffffffu, ep1, 0);
    TA0(59);
    auto load_wq = [&](uint32_t dst, uint32_t bar, int s) {
      const int lane = tid_now() & 31;
      const __nv_bfloat16* src = wqkv + (32 * s + lane) * NQKV + 72 * j + (rank ? 0 : 64);
      if (elect_one()) tma_load_3d(dst, &mp.wq, bar, 72 * j + 8 * rank, 32 * s, 0);
      if (elect_one()) tma_load_3d(dst + 8192, &mp.wq, bar, 72 * j + 8 * rank, 32 * s + 16, 0);
#pragma unroll
      for (int c = 0; c < 3; ++c)
        cp_async16(dst + (lane >> 4) * 8192 + 6144 + (lane & 15) * 128 + ((c ^ (lane & 7)) << 4), src + c * 576);
      cp_async_arrive(bar);
      __syncwarp();
      if (elect_one()) mbar_expect_tx(bar, 12288);
    };
    if (warp == 8) {
      int p = 2;
      uint32_t ph = 1;
      const int f0 = j * 576;
      int xi = X_EARLY;
#pragma unroll 1
      for (int L = 0; L < NLAYERS; ++L) {
#pragma unroll 1
        for (int s = 0; s < 18; ++s) {
          const uint32_t bar = sb + B_FULL + 8 * p;
          mbar_wait(bar + (B_EMPTY - B_FULL), ph);
          TR(s);
          if (L == 0 || !IMG) {
            load_wq(sb + RING + p * SLOT, bar, s);
            if (L == 0 && elect_one()) {
#pragma unroll 1
              for (int e = (X_SCHED >> (2 * s)) & 3; e > 0; --e, ++xi)
                tma_load_3d_mc(sb + rank * HALF + xi * TILE, &mp.x0, sb + B_FX + 72 * rank + 8 * xi, xi * 64, rb * 64 + rank * 32, 0);
              const int u = (s - GU_PF0) * 8 + (rb >> 1);
              if (s >= GU_PF0 && u < GU_PFN) tma_prefetch_2d((rb & 1) ? &mp.wu : &mp.wg, f0 + 64 * (u % 3), 64 * (u / 3));
            }
          } else if (elect_one()) {
            bulk_load(sb + RING + p * SLOT, g_wimg + (j * 18 + s) * 1024, SLOT, bar);
            mbar_expect_tx(bar, SLOT);
          }
          if (++p == 5) p = 0;
          if (p == 2) ph ^= 1;
        }
#pragma unroll 1
        for (int s = 0; s < 5; ++s) {
          const int cx = s ? 64 * (2 * s - 1 + rank) : 0;
          mbar_wait(sb + B_EMPTY + 8 * s, ph);
          if (elect_one()) {
            if (s) tma_load_2d(sb + RING + (2 * s - 1) * WOA, &mp.wo, sb + B_FULL + 8 * s, cx, 72 * j);
            tma_load_2d(sb + RING + 2 * s * WOA, &mp.wo, sb + B_FULL + 8 * s, cx, 72 * (s ? j ^ 1 : j));
            mbar_expect_tx(sb + B_FULL + 8 * s, s ? 2 * WOA : WOA);
          }
          if (s == 1) ph ^= 1;
        }
        {
          int cx = f0, cy = 0;
#pragma unroll 1
          for (int n = 0; n < 81; ++n) {
            const uint32_t dst = sb + RING + p * SLOT, bar = sb + B_FULL + 8 * p;
            if (n == (rank ? R1_N : R0_N)) {
              mbar_wait(sb + B_ST + 72 + 8, 0);
              fence_proxy_async();
              if (elect_one()) tma_reduce_3d(&mp.r, sb + HALF + (1 + rank) * TILE, 64 + 64 * rank, rb * 64 + 32, 0);
              bulk_commit();
              if (!rank) {
                bulk_wait<0>();
                asm volatile("bar.arrive 8, 64;" ::: "memory");
              }
              mbar_wait(sb + B_ST + 8, 0);
              fence_proxy_async();
              if (elect_one()) tma_reduce_3d(&mp.r, sb + (1 + rank) * TILE, 64 + 64 * rank, rb * 64, 0);
              bulk_commit();
            }
            mbar_wait(bar + (B_EMPTY - B_FULL), ph);
            if (elect_one()) tma_load_2d(dst, &mp.wg, bar, cx, cy);
            if (elect_one()) tma_load_2d(dst + 8192, &mp.wu, bar, cx, cy);
            if (elect_one()) mbar_expect_tx(bar, 16384);
            if (n == (rank ? R1_N : R0_N)) {
              bulk_wait<0>();
              if (rank) asm volatile("bar.arrive 8, 64;" ::: "memory");
              asm volatile("bar.arrive 7, 64;" ::: "memory");
            }
            if (n < 26) {
              cx += 64;
              if (cx == f0 + 192) {
                cx = f0;
                cy += 64;
              }
            } else if ((cy += 64) == 576) {
              cy = 0;
              cx += 64;
            }
            if (++p == 5) p = 0;
            if (p == 2) ph ^= 1;
          }
        }
        {
          int cx = 0, cy = f0;
#pragma unroll 1
          for (int n = 35; n > -6; --n) {
            const uint32_t dst = p < 5 ? sb + RING + p * SLOT : sb + 2 * TILE + p * TILE, bar = sb + B_FULL + 8 * p;
            mbar_wait(bar + (B_EMPTY - B_FULL), ph);
            if (elect_one()) tma_load_2d(dst, &mp.wd, bar, cx, cy);
            if ((cy += 64) == f0 + 576) {
              cy = f0;
              cx += 64;
            }
            if (n > -5 && elect_one()) tma_load_2d(dst + (p < 5 ? 8192 : HALF), &mp.wd, bar, cx, cy);
            if (elect_one()) mbar_expect_tx(bar, n > -5 ? 16384 : 8192);
            if ((cy += 64) == f0 + 576) {
              cy = f0;
              cx += 64;
            }
            if (IMG && n == 8 && L + 1 < NLAYERS) poll_ge(&g_flag[FL_W + j], lds_u32(sb + S_EP) * 18u);
            if (++p == (n > 1 ? 7 : 5)) p = 0;
            if (p == 2) ph ^= 1;
          }
        }
      }
    } else if (warp == 9) {
      auto fetch = [&](const CUtensorMap* map, uint32_t mask) {
        const int lane = tid_now() & 31;
        if ((mask >> lane) & 1)
          tma_load_3d_mc(sb + rank * HALF + lane * TILE, map, sb + B_FX + 72 * rank + 8 * lane, lane * 64, rb * 64 + rank * 32, 0);
        __syncwarp();
      };
      if ((tid_now() & 31) < 18) mbar_expect_tx(sb + B_FX + 8 * (tid_now() & 31), TILE);
      fetch(&mp.x0, (1u << X_EARLY) - 1);
      sts_u32(sb + S_EP, ep1);
      TA0(10);
      {
        const int lane = tid_now() & 31;
        mbar_wait(sb + B_J, 0);
        float2 c = make_float2(0.f, 0.f);
#pragma unroll
        for (int w = 0; w < 8; ++w) {
          const float2 v = lds_f2(sb + OVF + w * 256 + lane * 8);
          c.x += v.x;
          c.y += v.y;
        }
        if (blockIdx.x < 108) *reinterpret_cast<float2*>(g_csq + (blockIdx.x & 3) * NQKV + (blockIdx.x >> 2) * 64 + 2 * lane) = c;
        asm volatile("bar.arrive 6, 96;" ::: "memory");
        if (elect_one()) signal_release(&g_flag[FL_J]);
        TA0(11);
        poll_ge(&g_flag[FL_J], ep1 * 128u);
        TA0(12);
        if (blockIdx.x == 0 && lane < 8) g_claim[lane] = 0u;
        if (lane < 18) {
          const float4 w = ldg_cg_f4(g_wsum + 72 * j + 4 * lane);
          sts_u4(sb + S_WS + lane * 16, __float_as_uint(w.x), __float_as_uint(w.y), __float_as_uint(w.z), __float_as_uint(w.w));
        }
      }
#pragma unroll 1
      for (int n = 0; n < 2 * NLAYERS - 1; ++n) {
        if (n < NLAYERS) {
#pragma unroll 1
          for (int c = tid_now() & 31; c < 54; c += 32) {
            const int part = c / 18, i = c - 18 * part;
            const float* src = g_csq + part * 576 + 72 * j + 4 * (rank ? (i + 2) % 18 : i);
            float4 a = ldg_cg_f4(src), b = ldg_cg_f4(src + NQKV), d = ldg_cg_f4(src + 2 * NQKV);
            a.x += b.x; a.y += b.y; a.z += b.z; a.w += b.w;
            b = ldg_cg_f4(src + 3 * NQKV);
            a.x += b.x + d.x; a.y += b.y + d.y; a.z += b.z + d.z; a.w += b.w + d.w;
            const uint32_t h0 = pack_bf16(a.x, a.y), h1 = pack_bf16(a.z, a.w);
            const uint32_t ad = (i < 16 ? part * 256 + (((i >> 1) ^ (2 * part)) << 4) : 768 + ((part ^ 6) << 4)) + (i & 1) * 8;
            sts_f2(sb + OVF + ad, __uint_as_float(h0), __uint_as_float(h1));
            sts_f2(sb + OVF + (ad ^ 144), __uint_as_float(pack_bf16(a.x - bf_lo(h0), a.y - bf_hi(h0))),
                   __uint_as_float(pack_bf16(a.z - bf_lo(h1), a.w - bf_hi(h1))));
          }
          const int lane = tid_now() & 31;
          if (lane < 10) sts_u4(sb + OVF + 768 + (lane & 1) * 128 + (((3 + (lane >> 1)) ^ 6 ^ (lane & 1)) << 4), 0u, 0u, 0u, 0u);
          fence_proxy_async();
          warp_arrive(sb + B_AUX);
        }
        {
          const int lane = tid_now() & 31;
          const uint32_t bar = sb + B_FX + 8 * min(lane, 17);
#pragma unroll 1
          for (int it = 0; it < SPIN_MAX; ++it)
            if (__all_sync(0xffffffffu, mbar_test(bar, n & 1))) break;
          if (lane < 18) mbar_expect_tx(bar, TILE);
        }
        const unsigned int* fl = &g_flag[n * 512 + rb * 32 + rank * 16 + (tid_now() & 15)];
        if (LAZY) mbar_wait(sb + B_ST + 72 * rank, n & 1);
        uint32_t todo = 0x1FFu;
#pragma unroll 1
        for (int it = 0; todo && it < SPIN_MAX; ++it) {
          unsigned int v;
          asm volatile("ld.relaxed.gpu.global.u32 %0, [%1];" : "=r"(v) : "l"(fl) : "memory");
          const uint32_t ready = __ballot_sync(0xffffffffu, (int)(v - ep1 * 8u) >= 0) & todo;
          if (LAZY > 1 && (n & 1) && !ready && (todo & 0x7F)) __nanosleep(300);
          if (ready) {
            todo &= ~ready;
            fetch(&mp.r, ready);
          }
        }
      }
      uint32_t bid;
      asm volatile("mov.u32 %0, %%ctaid.x;" : "=r"(bid));
      if (elect_one()) g_epoch[bid] = ep1;
    } else {
      const int h = warp & 1;
      if (h) {
        const int lane = tid_now() & 31;
#pragma unroll 1
        for (int i = 0; i < 12; ++i) st_tagged(g_halo + (rb * 8 + j) * 384 + i * 32 + lane, 0u, 0u, 0u, 2 * ep1 - 1);
        if (lane < 16) st_tagged(g_stat + rb * 128 + (lane >> 3) * 64 + 8 * j + (lane & 7), 0u, 0u, 0u, 4 * ep1 - 1);
      }

      auto copy = [&](int hh, int c) {
        if (elect_one()) tma_store_3d(&mp.r, sb + hh * HALF + c * TILE, 64 * c, rb * 64 + hh * 32, 0);
        bulk_commit();
        bulk_wait<0>();
        __syncwarp();
        if (c < 3) asm volatile("fence.acq_rel.gpu;" ::: "memory");
      };
      float s1 = 0.f, s2 = 0.f;
      int kb = 0;
      uint32_t hn = 0;
      auto tile_stats = [&]() {
        const int lane = tid_now() & 31;
        const uint32_t ad = sb + h * HALF + kb * TILE + j * 1024 + (lane & 28) * 32 + (lane & 7) * 16;
        const uint4 u = lds_u4(ad), v = lds_u4(ad ^ 64);
        const uint32_t w[8] = {u.x, u.y, u.z, u.w, v.x, v.y, v.z, v.w};
        float a = 0.f, b = 0.f;
#pragma unroll
        for (int e = 0; e < 8; ++e) {
          const float lo = bf_lo(w[e]), hi = bf_hi(w[e]);
          s1 += lo;
          a += hi;
          s2 = fmaf(lo, lo, s2);
          b = fmaf(hi, hi, b);
        }
        s1 += a;
        s2 += b;
        ++kb;
      };
      unsigned int* fl = &g_flag[rb * 32];
#pragma unroll 1
      for (int n = 0; n < 2 * NLAYERS; ++n, fl += 512) {
        const int L = n >> 1;
        (void)L;
        {
          const int lane = tid_now() & 31;
#pragma unroll 1
          while (kb < 8 + (n & 1)) {
            mbar_wait(sb + B_FX + 72 * h + 8 * kb, n & 1);
            tile_stats();
            if (n == 0 && kb == j + 1) copy(h, j);
          }
          s1 = quad_sum(s1) * ((n & 1) ? 1.0f / DM : 1.0f / 512);
          s2 = fmaf(s1 * s1, (n & 1) ? -576.f : -512.f, quad_sum(s2));
          if (n & 1) {
            s2 = inv_sd(s2 * (1.0f / DM));
            s2 *= s2;
          }
          uint4* gs = g_stat + rb * 128 + h * 64;
          const uint32_t tag = 4 * ep1 + n;
          if ((lane & 3) == 0) st_tagged(gs + 8 * j + (lane >> 2), __float_as_uint(s1) & ~128u, __float_as_uint(s2) & ~128u, 0u, tag);
          s1 = s2 = 0.f;
          kb = 0;
          TA(14 + (n & 1) * 2);
          uint4 u, v;
#pragma unroll 1
          for (int it = 0; it < SPIN_MAX; ++it) {
            u = ld_tagged(gs + 2 * lane);
            v = ld_tagged(gs + 2 * lane + 1);
            if (__all_sync(0xffffffffu, u.w == tag && v.w == tag)) break;
          }
          if (n == 0) named_bar_sync(6, 96);
          if (n & 1) {
            sts_u32(sb + TAB + h * 512 + lane * 16 + 4, u.y);
            sts_u32(sb + TAB + h * 512 + lane * 16 + 12, v.y);
          } else {
            sts_u4(sb + TAB + h * 512 + lane * 16, u.x, u.y, v.x, v.y);
            fence_proxy_async();
          }
          warp_arrive(sb + B_SR);
          TA(15 + (n & 1) * 2);
        }
        if (!((n & 1) | h)) {
          const int lane = tid_now() & 31;
          const uint32_t dst = sb + (2 - rank) * TILE;
          mbar_wait(sb + B_QK, L);
          TA(18);
          if (rb) {
            auto attempt = [&](uint32_t b) {
              if (elect_one()) {
                mbar_expect_tx(sb + B_HP + 8 * b, 6144);
                bulk_load(dst, g_halo + (rb * 8 - 8 + j) * 384, 6144, sb + B_HP + 8 * b);
              }
            };
            attempt(hn & 1);
            __nanosleep(100);
#pragma unroll 1
            for (int it = 0; it < SPIN_MAX; ++it) {
              attempt(~hn & 1);
              mbar_wait(sb + B_HP + 8 * (hn & 1), (hn >> 1) & 1);
              ++hn;
              uint32_t bad = 0;
#pragma unroll
              for (int i = 0; i < 12; ++i) bad |= lds_u32(dst + lane * 16 + 12 + i * 512) ^ (2 * ep1 + L);
              if (__all_sync(0xffffffffu, bad == 0)) break;
            }
          } else {
#pragma unroll 1
            for (int i = 0; i < 12; ++i) sts_u4(dst + lane * 16 + i * 512, 0u, 0u, 0u, 0u);
            __syncwarp();
          }
          if (lane < 2) mbar_arrive(sb + B_NB + 16 * lane);
          TA(19);
          if (rb) {
            mbar_wait(sb + B_HP + 8 * (hn & 1), (hn >> 1) & 1);
            ++hn;
          }
        }
        if (n == 0 && h && (j & 5) == 0) {
          mbar_wait(sb + B_FX + 36 * j + 64, 0);
          copy(j >> 1, 8);
        }
        auto send = [&](int hh, int c) {
          TA(20 + (n & 1) * 20 + c);
          fence_proxy_async();
          if (elect_one()) tma_reduce_3d(&mp.r, sb + hh * HALF + c * TILE, 64 * c, rb * 64 + hh * 32, 0);
          bulk_commit();
        };
        if (!(n & 1)) {
          uint32_t tnext, t;
#pragma unroll 1
          for (int i = 0; i < 5; ++i) {
            const int c = i ? 2 * i - 1 + rank : 0;
            if (i == 1) {
              TA(20 + c);
              named_bar_sync(7 + h, 64);
              if (elect_one()) signal_release(fl + 16 * h + c, 2);
              TA(30 + c);
              continue;
            }
            mbar_wait(sb + B_ST + 72 * h + 8 * i, 0);
            while (true) {
              asm volatile("mov.u32 %0, %%clock;" : "=r"(t));
              if (i == 0 || (int)(t - tnext) >= 0) break;
              __nanosleep(40);
            }
            tnext = i ? tnext + PACE : t + PACE0 + rank * PACE_R;
            if (i == (n ? 4 : 2)) {
              mbar_wait(sb + B_FX, 1);
              mbar_wait(sb + B_FX + 72, 1);
            }
            send(h, c);
            bulk_wait<0>();
            if (elect_one()) signal_release(fl + 16 * h + c, i ? 2 : 1);
            TA(30 + c);
          }
        } else {
          if (IMG && n == 1 && NLAYERS > 1 && !h) {
#pragma unroll 1
            for (int s = rb; s < 18; s += 16) {
              const uint32_t bar = sb + B_HP + 8 * (hn & 1), dst = sb + (s >> 4) * HALF + 5 * TILE;
              mbar_wait(sb + B_ST + 72 * (s >> 4), 1);
              load_wq(dst, bar, s);
              mbar_wait(bar, (hn >> 1) & 1);
              ++hn;
              fence_proxy_async();
              __syncwarp();
              if (elect_one()) bulk_store(g_wimg + (j * 18 + s) * 1024, dst, SLOT);
            }
          }
#pragma unroll 1
          for (int a = h ^ 1; a < 9; a += 2) {
            mbar_wait(sb + B_ST + 72 + 8 * a, 1);
            send(1, a);
            mbar_wait(sb + B_ST + 8 * a, 1);
            send(0, a);
            if (n < 2 * NLAYERS - 1) {
              bulk_wait<0>();
              if (elect_one()) {
                signal_release(fl + 16 + a);
                signal_relaxed(fl + a);
                if (IMG && a == 1) {
                  signal_relaxed(&g_flag[FL_W + j], rb < 2 ? 2 : 1);
                  mbar_arrive(sb + B_S1);
                }
              }
              TA(50 + a);
#pragma unroll 1
              while (kb < min(a - 1, ST_END)) {
                mbar_wait(sb + B_FX + 72 * h + 8 * kb, 0);
                tile_stats();
              }
            }
          }
          bulk_wait<0>();
        }
      }
    }
  } else {
    {
      const int t = threadIdx.x, lane = t & 31;
      uint4 sq[5], so[3];
      if (t < 16 * X_PF) asm volatile("prefetch.global.L2 [%0];" ::"l"(x0 + (size_t)(blockIdx.x * 16 + (t & 15)) * DM + (t >> 4) * 64));
#pragma unroll
      for (int i = 0; i < 5; ++i)
        sq[i] = ldg_u4(wqkv + (size_t)((blockIdx.x & 3) + (t >> 3) * 4 + 128 * i) * NQKV + (blockIdx.x >> 2) * 64 + (t & 7) * 8,
                       blockIdx.x < 108 && (i < 4 || t < 128));
#pragma unroll
      for (int i = 0; i < 3; ++i)
        so[i] = ldg_u4(wo + (size_t)((blockIdx.x - 32) * 6 + warp) * DM + (i * 32 + lane) * 8,
                       blockIdx.x >= 32 && warp < 6 && (i < 2 || lane < 8));
      asm volatile("setmaxnreg.inc.sync.aligned.u32 240;");
      float c[8];
#pragma unroll
      for (int e = 0; e < 8; ++e) c[e] = 0.f;
#pragma unroll
      for (int i = 0; i < 5; ++i) {
        c[0] += bf_lo(sq[i].x); c[1] += bf_hi(sq[i].x); c[2] += bf_lo(sq[i].y); c[3] += bf_hi(sq[i].y);
        c[4] += bf_lo(sq[i].z); c[5] += bf_hi(sq[i].z); c[6] += bf_lo(sq[i].w); c[7] += bf_hi(sq[i].w);
      }
#pragma unroll
      for (int n = 4; n >= 2; n >>= 1) {
        const bool up = lane & (4 * n);
#pragma unroll
        for (int e = 0; e < n; ++e) c[e] = (up ? c[e + n] : c[e]) + __shfl_xor_sync(0xffffffffu, up ? c[e] : c[e + n], 4 * n);
      }
      sts_f2(sb + OVF + warp * 256 + (lane & 7) * 32 + (lane & 24), c[0], c[1]);
      float r = sum8(so[0]) + sum8(so[1]) + sum8(so[2]);
#pragma unroll
      for (int o = 1; o < 32; o <<= 1) r += __shfl_xor_sync(0xffffffffu, r, o);
      if (lane == 0 && blockIdx.x >= 32 && warp < 6) g_wsum[(blockIdx.x - 32) * 6 + warp] = r;
      cluster_wait();
      warp_arrive(sb + B_J);
      TA0(13);
    }
#pragma unroll 1
    for (uint32_t L = 0; L < NLAYERS; ++L) {
      {
        const int wg = warp >> 2;
        float acc[108];
        const uint32_t da0 = desc_lo_a(sb + wg * HALF), db0 = desc_lo_b(sb + RING, 2048);
        int p = 2;
        uint32_t ph = L;
        auto step = [&](int kb, auto U, auto FIRST) {
          constexpr int u = decltype(U)::value, first = decltype(FIRST)::value == 1;
          constexpr bool last = decltype(FIRST)::value == 2;
          wgmma_fence();
#pragma unroll
          for (int k = 0; k < 2; ++k)
            wgmma_ss<216>(acc, desc_from_lo(da0 + kb * 512 + u * 4 + k * 2), desc_from_lo(db0 + p * 1024 + k * 512), !first || u || k);
          wgmma_commit();
          if (last && wg) asm volatile("bar.arrive 5, 256;" ::: "memory");
          const int prev = p == 0 ? 4 : p - 1;
          if (++p == 5) p = 0;
          if (p == 2) ph ^= 1;
          if (!last) {
            if (u) mbar_wait2(sb + B_FX + 72 * wg + 8 * kb + 8, 0, sb + B_FULL + 8 * p, ph);
            else mbar_wait(sb + B_FULL + 8 * p, ph);
          }
          if (!first || u) {
            wgmma_wait<1>();
            release_slot(sb, prev);
          }
        };
        mbar_wait2(sb + B_FX + 72 * wg, 0, sb + B_FULL + 8 * p, ph);
        TR(1);
        step(0, IC<0>{}, IC<1>{});
        step(0, IC<1>{}, IC<1>{});
        float s1[2] = {0.f, 0.f}, s2[2] = {0.f, 0.f};
        bool todo = true;
        const int stop = wg ? 8 : Q_H;
        auto last_tile = [&]() {
          const int lane = tid_now() & 31;
#pragma unroll
          for (int r = 0; r < 2; ++r) {
            const uint32_t ad = sb + wg * HALF + 8 * TILE + (warp & 3) * 2048 + r * 1024 + (lane & 28) * 32 + (lane & 7) * 16;
            const uint4 u = lds_u4(ad), v = lds_u4(ad ^ 64);
            const uint32_t w[8] = {u.x, u.y, u.z, u.w, v.x, v.y, v.z, v.w};
            float a = 0.f, b = 0.f, c = 0.f, d = 0.f;
#pragma unroll
            for (int e = 0; e < 8; ++e) {
              const float lo = bf_lo(w[e]), hi = bf_hi(w[e]);
              a += lo;
              b += hi;
              c = fmaf(lo, lo, c);
              d = fmaf(hi, hi, d);
            }
            s1[r] = quad_sum(a + b) * (1.0f / 64);
            s2[r] = fmaf(s1[r] * s1[r], -64.f, quad_sum(c + d));
          }
          todo = false;
        };
#pragma unroll 1
        for (int kb = 1; kb < 9; ++kb) {
          TR(1 + kb);
          if (Q_H < 8 && kb == stop) mbar_wait(sb + B_FX + 72 * wg + 64, 0);
          if (todo && kb >= (wg ? Q_ST1 : Q_ST0) && __all_sync(0xffffffffu, mbar_test(sb + B_FX + 72 * wg + 64, 0))) last_tile();
          if (kb == stop) break;
          step(kb, IC<0>{}, IC<0>{});
          step(kb, IC<1>{}, IC<0>{});
        }
        const int tid = tid_now(), lane = tid & 31, g = lane >> 2, q = lane & 3;
        if (lane == 0 && wg == 0) mbar_arrive(sb + B_QK);
        mbar_wait2(sb + B_SR, 0, sb + B_AUX, L);
        float2 st0 = lds_f2(sb + TAB + (warp * 16 + g) * 8), st1 = lds_f2(sb + TAB + (warp * 16 + g) * 8 + 64);
        s1[0] -= st0.x;
        s1[1] -= st1.x;
        st0.x = fmaf(s1[0], 1.0f / 9, st0.x);
        st1.x = fmaf(s1[1], 1.0f / 9, st1.x);
        st0.y = fmaf(s1[0] * s1[0], 512.f / 9, st0.y + s2[0]);
        st1.y = fmaf(s1[1] * s1[1], 512.f / 9, st1.y + s2[1]);
        if (wg == 0) named_bar_sync(5, 256);
        wgmma_fence();
        wgmma_rs<216>(acc, q ? 0u : pack_bf16(-st0.x, -st0.x), q ? 0u : pack_bf16(-st1.x, -st1.x), 0u, 0u, desc_sbo(desc_lo_b(sb + OVF, 256), 0), 1);
        wgmma_commit();
        if (Q_H < 8) {
#pragma unroll 1
          for (int kb = stop; kb < 8; ++kb) {
            step(kb, IC<0>{}, IC<0>{});
            step(kb, IC<1>{}, IC<0>{});
          }
        }
        step(8, IC<0>{}, IC<0>{});
        step(8, IC<1>{}, IC<2>{});
        TR(10);
        st0.y = inv_sd(st0.y * (1.0f / DM));
        st1.y = inv_sd(st1.y * (1.0f / DM));
        const uint32_t ep1 = lds_u32(sb + S_EP), role = lds_u32(sb + S_ROLE);
        const bool first = (warp & 5) == 0 && role < 4;
        const bool e0 = 2 * q > g, e1 = 2 * q + 1 > g;
        float fs[2][2], fp[2][2], fb[2];
        {
          const float k0 = __shfl_sync(0xffffffffu, st0.y, 8 * q), k1 = __shfl_sync(0xffffffffu, st0.y, 8 * q + 4);
          const float c = 0.23570226039551584f * 1.4426950408889634f;
          fp[0][0] = e0 ? 1.f : k0;
          fp[0][1] = e1 ? 1.f : k1;
          fp[1][0] = e0 ? k0 : 1.f;
          fp[1][1] = e1 ? k1 : 1.f;
#pragma unroll
          for (int i = 0; i < 4; ++i) fs[i >> 1][i & 1] = fp[i >> 1][i & 1] * ((i >> 1) ? st1.y : st0.y) * c;
          fb[0] = first && e0 ? -INFINITY : 0.f;
          fb[1] = first && e1 ? -INFINITY : 0.f;
        }
        const int sw = (warp & 1) ? warp + 3 : warp + 1;
        const uint64_t nbp = sw >= 8 ? (uint64_t)(g_halo + (role * 2 + rank) * 384 + (warp & 2) * 96 + lane)
                                     : (uint64_t)(smem + (sw >> 2) * HALF + (2 + 2 * (sw & 1) - rank) * TILE + (sw & 2) * 1536 + lane * 16);
        const uint32_t nbb = lane ? mapa(sb + B_RX + 8 * wg, rank ^ 1) : mapa(sb + B_NB + 8 * (sw & 7), rank);
        const bool nba = lane ? lane == 1 : sw < 8;
        if (tid == 128 * wg) mbar_expect_tx(sb + B_OX + 8 * wg, 10240);
        __syncwarp();
        wgmma_wait<0>();
        release_slot(sb, 4);
        TS(1);
        uint32_t Q[2][9], K[3][9], V[3][9];
        auto pack = [&](auto R) {
          constexpr int r = decltype(R)::value;
#pragma unroll
          for (int i = 0; i < 9; ++i) {
            const int c = (i + 9 - r) % 9, jv = c < 8 ? 64 + 4 * c : 104;
            V[2][i] = movm(pack_bf16(acc[jv + 2] * st1.y, acc[jv + 3] * st1.y));
          }
#pragma unroll
          for (int i = 0; i < 9; ++i) {
            const int c = (i + 9 - r) % 9, jk = c < 8 ? 32 + 4 * c : 100;
            K[2][i] = pack_bf16(acc[jk + 2] * st1.y, acc[jk + 3] * st1.y);
          }
#pragma unroll
          for (int i = 0; i < 6; ++i) {
            const uint32_t(&d)[9] = i < 3 ? K[2] : V[2];
            st_tagged_any(nbp + i * 512, d[3 * (i % 3)], d[3 * (i % 3) + 1], d[3 * (i % 3) + 2], 2 * ep1 + L);
          }
          __syncwarp();
          mbar_arrive_if(nbb, nba);
#pragma unroll
          for (int i = 0; i < 9; ++i) {
            const int c = (i + 9 - r) % 9, jq = c < 8 ? 4 * c : 96, jk = c < 8 ? 32 + 4 * c : 100, jv = c < 8 ? 64 + 4 * c : 104;
            V[1][i] = movm(pack_bf16(acc[jv], acc[jv + 1]));
            Q[0][i] = pack_bf16(acc[jq], acc[jq + 1]);
            Q[1][i] = pack_bf16(acc[jq + 2], acc[jq + 3]);
            K[1][i] = pack_bf16(acc[jk], acc[jk + 1]);
          }
        };
        if (rank) pack(IC<1>{});
        else pack(IC<0>{});
        uint32_t qf[4][2], ql[4][2];
        float sc[4][3][4];
        auto logits = [&](int t) {
#pragma unroll
          for (int h = 0; h < 4; ++h) {
            mma_1688(sc[h][t], ql[h][0], ql[h][1], K[t][2 * h + 2]);
            mma_16816(sc[h][t], qf[h][0], qf[h][1], Q[0][2 * h + 1], Q[1][2 * h + 1], K[t][2 * h], K[t][2 * h + 1]);
          }
        };
#pragma unroll
        for (int i = 0; i < 8; ++i) {
          qf[i >> 1][i & 1] = q >= (i >> 1) ? Q[i & 1][i & 6] : 0u;
          ql[i >> 1][i & 1] = q <= (i >> 1) ? Q[i & 1][(i & 6) + 2] : 0u;
        }
        logits(1);
        logits(2);
        float2 ws[9];
#pragma unroll
        for (int i = 0; i < 9; ++i) ws[i] = lds_f2(sb + S_WS + i * 32 + 8 * q);
        uint32_t of[9][2];
        float o0[9][2];
        auto rows = [&](auto R, float(&o)[9][2]) {
          constexpr int r = decltype(R)::value;
          float pr[4][2], mx[4];
#pragma unroll
          for (int h = 0; h < 4; ++h) {
            pr[h][0] = fmaf(e0 ? sc[h][r][2 * r] : sc[h][r + 1][2 * r], fs[r][0], r ? 0.f : fb[0]);
            pr[h][1] = fmaf(e1 ? sc[h][r][2 * r + 1] : sc[h][r + 1][2 * r + 1], fs[r][1], r ? 0.f : fb[1]);
            mx[h] = fmaxf(pr[h][0], pr[h][1]);
          }
#pragma unroll
          for (int i = 0; i < 8; ++i) mx[i & 3] = fmaxf(mx[i & 3], __shfl_xor_sync(0xffffffffu, mx[i & 3], 1 + (i >> 2)));
#pragma unroll
          for (int h = 0; h < 4; ++h) {
#pragma unroll
            for (int e = 0; e < 2; ++e) asm("ex2.approx.ftz.f32 %0, %1;" : "=f"(pr[h][e]) : "f"(pr[h][e] - mx[h]));
            mx[h] = pr[h][0] + pr[h][1];
            pr[h][0] *= fp[r][0];
            pr[h][1] *= fp[r][1];
          }
#pragma unroll
          for (int i = 0; i < 8; ++i) mx[i & 3] += __shfl_xor_sync(0xffffffffu, mx[i & 3], 1 + (i >> 2));
          const uint32_t me = (e0 ? 0xFFFFu : 0u) | (e1 ? 0xFFFF0000u : 0u);
          uint32_t pp[4];
#pragma unroll
          for (int h = 0; h < 4; ++h) {
            pp[h] = pack_bf16(pr[h][0], pr[h][1]);
            asm("rcp.approx.ftz.f32 %0, %1;" : "=f"(mx[h]) : "f"(mx[h]));
          }
#pragma unroll
          for (int i = 0; i < 9; ++i) {
            const int h = i < 4 ? 0 : i < 5 ? 1 : 2;
            float d[4];
            mma_16816_z(d, pp[h] & me, pp[h + 1] & me, pp[h] & ~me, pp[h + 1] & ~me, V[r][i], V[r + 1][i]);
            const bool up = i == 2 * h + 2 ? q > h : i > 2 * h + 2;
            const float inv = up ? mx[h + 1] : mx[h];
            o[i][0] = (up ? d[2] : d[0]) * inv;
            o[i][1] = (up ? d[3] : d[1]) * inv;
            of[i][r] = pack_bf16(o[i][0], o[i][1]);
          }
        };
        auto shift = [&](const float(&o)[9][2]) {
          float a = 0.f, b = 0.f, c = 0.f;
#pragma unroll
          for (int i = 0; i < 3; ++i) {
            a = fmaf(o[i][0], ws[i].x, fmaf(o[i][1], ws[i].y, a));
            b = fmaf(o[i + 3][0], ws[i + 3].x, fmaf(o[i + 3][1], ws[i + 3].y, b));
            c = fmaf(o[i + 6][0], ws[i + 6].x, fmaf(o[i + 6][1], ws[i + 6].y, c));
          }
          return a + b + c;
        };
        rows(IC<1>{}, o0);
        float sh1 = shift(o0);
        mbar_wait3(sb + B_FULL, L ^ 1, sb + B_RX + 8 * wg, L, sb + B_NB + 8 * warp, L);
#pragma unroll
        for (int i = 0; i < 6; ++i) {
          const uint4 u = lds_u4(sb + wg * HALF + (2 + 2 * (warp & 1) - rank) * TILE + (warp & 2) * 1536 + lane * 16 + i * 512);
          uint32_t(&d)[9] = i < 3 ? K[0] : V[0];
          d[3 * (i % 3)] = u.x;
          d[3 * (i % 3) + 1] = u.y;
          d[3 * (i % 3) + 2] = u.z;
        }
        TS(3);
        logits(0);
        rows(IC<0>{}, o0);
        TS(5);
        float wa[3][32];
        const uint32_t dw0 = desc_lo_b(sb + RING, 0);
        wgmma_fence();
#pragma unroll
        for (int k = 0; k < 5; ++k)
          wgmma_rs<64>(wa[0], of[2 * k][0], of[2 * k][1], k < 4 ? of[2 * k + 1][0] : 0u, k < 4 ? of[2 * k + 1][1] : 0u,
                       desc_sbo(dw0 + k * 128, k < 4 ? 1024 : 0), k);
        wgmma_commit();
        const uint32_t xa = sb + wg * HALF + 3 * TILE + (warp & 3) * 2048 + lane * 16;
        const uint32_t xr = mapa(xa + (rank ^ 1) * TILE, rank ^ 1), xb = mapa(sb + B_OX + 8 * wg, rank ^ 1);
#pragma unroll
        for (int i = 0; i < 4; ++i) st_async_u4(xr + i * 512, xb, of[2 * i][0], of[2 * i][1], of[2 * i + 1][0], of[2 * i + 1][1]);
        float sh0 = fmaf(quad_sum(shift(o0)), 1.0f / DM, st0.x * 0.125f);
        sh1 = fmaf(quad_sum(sh1), 1.0f / DM, st1.x * 0.125f);
        st_async_u4(xr + 2 * TILE, xb, of[8][0], of[8][1], __float_as_uint(sh0), __float_as_uint(sh1));
        wgmma_wait<0>();
        stage_tile(wa[0], 1.f, -sh0, 1.f, -sh1, sb, 0, 0, 1);
        TS(6);
        uint4 xv[5];
        auto issue = [&](auto I, auto PART) {
          constexpr int i = decltype(I)::value, part = decltype(PART)::value;
          const uint32_t lo = dw0 + (2 * i - 1) * (WOA / 16);
          if (part & 1) mbar_wait(sb + B_FULL + 8 * i, (i == 1) ^ L);
          wgmma_fence();
          if (part & 1) {
#pragma unroll
            for (int k = 0; k < 4; ++k)
              wgmma_rs<64>(wa[i % 3], of[2 * k][0], of[2 * k][1], of[2 * k + 1][0], of[2 * k + 1][1], desc_sbo(lo + k * 128, 1024), k);
          }
          if (part & 2) {
            wgmma_rs<64>(wa[i % 3], of[8][0], of[8][1], xv[4].x, xv[4].y, desc_sbo(lo + 512, WOA), 1);
#pragma unroll
            for (int k = 0; k < 4; ++k)
              wgmma_rs<64>(wa[i % 3], xv[k].x, xv[k].y, xv[k].z, xv[k].w, desc_sbo(lo + WOA / 16 + k * 128, 1024), 1);
          }
          wgmma_commit();
        };
        issue(IC<1>{}, IC<1>{});
        if (q < 2) sts_u32(sb + TAB + (warp * 16 + g + 8 * q) * 8, __float_as_uint(q ? sh1 : sh0));
        mbar_wait(sb + B_OX + 8 * wg, L);
#pragma unroll
        for (int i = 0; i < 5; ++i) xv[i] = lds_u4(xa + rank * TILE + (i < 4 ? i * 512 : 2 * TILE));
        sh0 += __uint_as_float(xv[4].z);
        sh1 += __uint_as_float(xv[4].w);
        TS(4);
        issue(IC<1>{}, IC<2>{});
        wgmma_wait<0>();
        release_slot(sb, 0);
        stage_tile(wa[1], 1.f, -sh0, 1.f, -sh1, sb, 1 + rank, 1, 1);
        mbar_wait(sb + B_ST, 0);
        issue(IC<2>{}, IC<3>{});
        issue(IC<3>{}, IC<3>{});
        wgmma_wait<1>();
        release_slot(sb, 1);
        issue(IC<4>{}, IC<3>{});
        stage_tile(wa[2], 1.f, -sh0, 1.f, -sh1, sb, 3 + rank, 0, 0);
        wgmma_wait<1>();
        release_slot(sb, 2);
        stage_tile(wa[0], 1.f, -sh0, 1.f, -sh1, sb, 5 + rank, 0, 0);
        wgmma_wait<0>();
        release_slot(sb, 3);
        release_slot(sb, 4);
        stage_tile(wa[1], 1.f, -sh0, 1.f, -sh1, sb, 7 + rank, 2, 7);
        TS(7);
      }
      uint32_t hreg[9][16];
      {
        const int wg = warp >> 2;
        float acc[64];
        int p = 0;
        uint32_t ph = L;
        const uint32_t da0 = desc_lo_a(sb + wg * HALF), db0 = desc_lo_b(sb + RING, 8192);
        float prod[32];
        {
          float acc0[64], acc1[64], acc2[64];
#pragma unroll
          for (int i = 0; i < 64; ++i) acc0[i] = acc1[i] = acc2[i] = 0.f;
          auto step = [&](float(&d)[64], int kb, bool rel) {
            mbar_wait(sb + B_FULL + 8 * p, ph);
            wgmma_fence();
#pragma unroll
            for (int k = 0; k < 4; ++k)
              wgmma_ss<128>(d, desc_from_lo(da0 + kb * 512 + k * 2), desc_from_lo(db0 + p * 1024 + k * 128), 1);
            wgmma_commit();
            wgmma_wait<1>();
            release_slot(sb, p == 0 ? 4 : p - 1, rel);
            if (++p == 5) p = 0;
            if (p == 2) ph ^= 1;
          };
#pragma unroll 1
          for (int kb = 0; kb < 9; ++kb) {
            mbar_wait(sb + B_FX + 72 * wg + 8 * kb, 1);
            if (kb == 0) TS(9);
            TR(16 + kb);
            step(acc0, kb, kb > 0);
            step(acc1, kb, true);
            step(acc2, kb, true);
          }
#pragma unroll
          for (int i = 0; i < 16; ++i) {
            hreg[0][i] = pack_bf16(acc0[2 * i] * acc0[32 + 2 * i], acc0[2 * i + 1] * acc0[33 + 2 * i]);
            hreg[1][i] = pack_bf16(acc1[2 * i] * acc1[32 + 2 * i], acc1[2 * i + 1] * acc1[33 + 2 * i]);
          }
          mbar_wait(sb + B_FULL + 8 * p, ph);
          wgmma_wait<0>();
#pragma unroll
          for (int i = 0; i < 32; ++i) prod[i] = acc2[i] * acc2[32 + i];
        }
#pragma unroll
        for (int t = 2; t < 8; ++t)
#pragma unroll
          for (int i = 0; i < 16; ++i) hreg[t][i] = 0u;
        TS(10);
#pragma unroll 1
        for (int t = 3; t < 9; ++t) {
          wgmma_fence();
#pragma unroll
          for (int k = 0; k < 4; ++k)
            wgmma_ss<128>(acc, desc_from_lo(da0 + k * 2), desc_from_lo(db0 + p * 1024 + k * 128), k != 0);
          wgmma_commit();
          release_slot(sb, p == 0 ? 4 : p - 1);
#pragma unroll
          for (int i = 0; i < 32; ++i) asm volatile("" : "+f"(prod[i]));
#pragma unroll
          for (int i = 0; i < 16; ++i) hreg[8][i] = pack_bf16(prod[2 * i], prod[2 * i + 1]);
          if (++p == 5) p = 0;
          if (p == 2) ph ^= 1;
          mbar_wait(sb + B_FULL + 8 * p, ph);
#pragma unroll 1
          for (int kb = 1; kb < 9; ++kb) {
            wgmma_fence();
#pragma unroll
            for (int k = 0; k < 4; ++k)
              wgmma_ss<128>(acc, desc_from_lo(da0 + kb * 512 + k * 2), desc_from_lo(db0 + p * 1024 + k * 128), 1);
            wgmma_commit();
            if (kb == 1) {
#pragma unroll
              for (int tt = 2; tt < 8; ++tt)
                if (t == tt + 1) {
#pragma unroll
                  for (int i = 0; i < 16; ++i) asm volatile("mov.b32 %0, %1;" : "=r"(hreg[tt][i]) : "r"(hreg[8][i]));
                }
            }
            const int done = p == 0 ? 4 : p - 1;
            if (++p == 5) p = 0;
            if (p == 2) ph ^= 1;
            if (GU_PRE) mbar_wait(sb + B_FULL + 8 * p, ph);
            wgmma_wait<1>();
            release_slot(sb, done);
            if (!GU_PRE) mbar_wait(sb + B_FULL + 8 * p, ph);
          }
          wgmma_wait<0>();
#pragma unroll
          for (int i = 0; i < 32; ++i) prod[i] = acc[i] * acc[32 + i];
          TR(32 + t);
        }
#pragma unroll
        for (int i = 0; i < 16; ++i) hreg[8][i] = pack_bf16(prod[2 * i], prod[2 * i + 1]);
      }
      TS(11);
      {
        float accA[32], accB[32];
#pragma unroll
        for (int i = 16; i < 32; ++i) accB[i] = 0.f;
        int p = 1;
        uint32_t ph = L;
        const uint32_t db0 = desc_lo_b(sb + RING, 8192);
        int prev = 0, left = 35;
        auto stage = [&](auto S, auto NU, bool rel) {
          constexpr int s = decltype(S)::value;
          const uint32_t dlo = p < 5 ? db0 + p * 1024 : db0 - RING / 16 + 1024 + p * 512, dv = p < 5 ? 512 : HALF / 16;
          wgmma_fence();
#pragma unroll
          for (int v = 0; v < decltype(NU)::value; ++v) {
            const int u = 2 * s + v, kq = u % 9;
#pragma unroll
            for (int k = 0; k < 4; ++k)
              wgmma_rs<64>(u >= 9 ? accB : accA, hreg[kq][4 * k], hreg[kq][4 * k + 1], hreg[kq][4 * k + 2], hreg[kq][4 * k + 3],
                           desc_from_lo(dlo + v * dv + k * 128), (kq | k) != 0);
          }
          wgmma_commit();
          const int done = prev;
          prev = p;
          --left;
          if (++p == (left > 0 ? 7 : 5)) p = 0;
          if (p == 2) ph ^= 1;
          if (decltype(NU)::value == 2) mbar_wait(sb + B_FULL + 8 * p, ph ^ (p >= 5));
          if (rel) {
            wgmma_wait<1>();
            release_slot(sb, done, done < 5 || left > 1);
          }
        };
        stage(IC<0>{}, IC<2>{}, false);
        release_slot(sb, 0);
        mbar_wait(sb + B_SR, 1);
        release_slot(sb, 5);
        release_slot(sb, 6);
        const uint32_t ta = sb + TAB + warp * 128 + (tid_now() & 28) * 2;
        const float2 t0 = lds_f2(ta), t1 = lds_f2(ta + 64);
        const float m0 = t0.y, c0 = t0.x, m1 = t1.y, c1 = t1.x;
#pragma unroll 1
        for (int i = 0; i < 4; ++i) {
          stage(IC<1>{}, IC<2>{}, true);
          if (i) stage_tile<2, 4>(accB, m0, c0, m1, c1, sb, 2 * i - 1, 0, 0);
          stage(IC<2>{}, IC<2>{}, true);
          if (i) stage_done(sb, 2 * i - 1, 1);
          stage(IC<3>{}, IC<2>{}, true);
          stage(IC<4>{}, IC<2>{}, true);
          stage(IC<5>{}, IC<2>{}, true);
          stage_tile<0, 2>(accA, m0, c0, m1, c1, sb, 2 * i, 0, 0);
          TR(48 + 2 * i);
          stage(IC<6>{}, IC<2>{}, true);
          stage_tile<2, 4>(accA, m0, c0, m1, c1, sb, 2 * i, 0, 0);
          stage(IC<7>{}, IC<2>{}, true);
          stage_done(sb, 2 * i, 1);
          if (i == 3 && (tid_now() & 31) == 0) mbar_arrive(sb + B_XF);
          stage(IC<8>{}, IC<2>{}, true);
          stage(IC<0>{}, IC<2>{}, true);
          if (IMG && i == 2 && L + 1 < NLAYERS) mbar_wait(sb + B_S1, 0);
          if (i == 3) mbar_wait(sb + B_XF, L);
          stage_tile<0, 2>(accB, m0, c0, m1, c1, sb, 2 * i + 1, 0, 0);
          TR(49 + 2 * i);
        }
        stage(IC<1>{}, IC<2>{}, true);
        stage_tile<2, 4>(accB, m0, c0, m1, c1, sb, 7, 7, DN_LATE ? 0 : 1);
        stage(IC<2>{}, IC<2>{}, true);
        if (DN_LATE) stage_done(sb, 7, 1);
        stage(IC<3>{}, IC<2>{}, true);
        stage(IC<4>{}, IC<1>{}, true);
        wgmma_wait<0>();
        release_slot(sb, 1);
        stage_tile(accA, m0, c0, m1, c1, sb, 8, 8, 1);
        TR(56);
        TS(12);
      }
    }
  }
}

__global__ void probe_kernel() {}

typedef CUresult (*PFN_tmEncode)(CUtensorMap*, CUtensorMapDataType, cuuint32_t, void*, const cuuint64_t*,
                                 const cuuint64_t*, const cuuint32_t*, const cuuint32_t*, CUtensorMapInterleave,
                                 CUtensorMapSwizzle, CUtensorMapL2promotion, CUtensorMapFloatOOBfill);

static void encode_2d(PFN_tmEncode fn, CUtensorMap* m, const void* ptr, uint64_t inner, uint64_t outer, uint32_t box_inner,
                      uint32_t box_outer) {
  cuuint64_t dims[2] = {inner, outer};
  cuuint64_t strides[1] = {inner * 2};
  cuuint32_t box[2] = {box_inner, box_outer};
  cuuint32_t estr[2] = {1, 1};
  fn(m, CU_TENSOR_MAP_DATA_TYPE_BFLOAT16, 2, const_cast<void*>(ptr), dims, strides, box, estr,
     CU_TENSOR_MAP_INTERLEAVE_NONE, CU_TENSOR_MAP_SWIZZLE_128B, CU_TENSOR_MAP_L2_PROMOTION_L2_256B,
     CU_TENSOR_MAP_FLOAT_OOB_FILL_NONE);
}

static void encode_3d(PFN_tmEncode fn, CUtensorMap* m, const void* ptr, uint64_t d0, uint64_t d1, uint64_t d2, uint64_t s1,
                      uint64_t s2, uint32_t b0, uint32_t b1, uint32_t b2, CUtensorMapL2promotion prom) {
  cuuint64_t dims[3] = {d0, d1, d2};
  cuuint64_t strides[2] = {s1, s2};
  cuuint32_t box[3] = {b0, b1, b2};
  cuuint32_t estr[3] = {1, 1, 1};
  fn(m, CU_TENSOR_MAP_DATA_TYPE_BFLOAT16, 3, const_cast<void*>(ptr), dims, strides, box, estr, CU_TENSOR_MAP_INTERLEAVE_NONE,
     CU_TENSOR_MAP_SWIZZLE_128B, prom, CU_TENSOR_MAP_FLOAT_OOB_FILL_NONE);
}

}

extern "C" void kernel_launch(void* const* d_in, const int* in_sizes, int n_in, void* d_out, int out_size) {
  const __nv_bfloat16* x0 = (const __nv_bfloat16*)d_in[0];
  const __nv_bfloat16* wqkv = (const __nv_bfloat16*)d_in[1];
  const __nv_bfloat16* wo = (const __nv_bfloat16*)d_in[2];
  const __nv_bfloat16* wg = (const __nv_bfloat16*)d_in[4];
  const __nv_bfloat16* wu = (const __nv_bfloat16*)d_in[5];
  const __nv_bfloat16* wd = (const __nv_bfloat16*)d_in[6];
  static PFN_tmEncode enc = nullptr;
  if (!enc) {
    void* fn = nullptr;
    cudaDriverEntryPointQueryResult qr;
    cudaGetDriverEntryPoint("cuTensorMapEncodeTiled", &fn, cudaEnableDefault, &qr);
    enc = (PFN_tmEncode)fn;
  }
  Maps mp;
  encode_3d(enc, &mp.x0, x0, DM, SEQ / 2, 2, DM * 4, DM * 2, 64, 32, 2, CU_TENSOR_MAP_L2_PROMOTION_L2_256B);
  encode_3d(enc, &mp.r, d_out, DM, SEQ / 2, 2, DM * 4, DM * 2, 64, 32, 2, CU_TENSOR_MAP_L2_PROMOTION_L2_256B);
  encode_3d(enc, &mp.wq, wqkv, 576, 576, 3, NQKV * 2, 576 * 2, 64, 16, 3, CU_TENSOR_MAP_L2_PROMOTION_L2_128B);
  encode_2d(enc, &mp.wo, wo, DM, DM, 64, 72);
  encode_2d(enc, &mp.wg, wg, FF, DM, 64, 64);
  encode_2d(enc, &mp.wu, wu, FF, DM, 64, 64);
  encode_2d(enc, &mp.wd, wd, DM, FF, 64, 64);
  cudaFuncSetAttribute(mega_kernel, cudaFuncAttributeMaxDynamicSharedMemorySize, SMEM_BYTES);
  static int small_gpc = -1;
  if (small_gpc < 0) {
    cudaFuncSetAttribute(probe_kernel, cudaFuncAttributeMaxDynamicSharedMemorySize, SMEM_BYTES);
    cudaFuncSetAttribute(probe_kernel, cudaFuncAttributeNonPortableClusterSizeAllowed, 1);
    int n[2] = {0, 0};
    for (int i = 0; i < 2; ++i) {
      cudaLaunchConfig_t cfg = {};
      cfg.gridDim = dim3(128);
      cfg.blockDim = dim3(384);
      cfg.dynamicSmemBytes = SMEM_BYTES;
      cudaLaunchAttribute at;
      at.id = cudaLaunchAttributeClusterDimension;
      at.val.clusterDim.x = 8 << i;
      at.val.clusterDim.y = at.val.clusterDim.z = 1;
      cfg.attrs = &at;
      cfg.numAttrs = 1;
      if (cudaOccupancyMaxActiveClusters(&n[i], probe_kernel, &cfg) != cudaSuccess) cudaGetLastError();
    }
    small_gpc = n[0] == 15 && n[1] == 7;
  }
  mega_kernel<<<128, 384, SMEM_BYTES, cudaStreamPerThread>>>(mp, x0, wqkv, wo, (__nv_bfloat16*)d_out, small_gpc);
}
```

```cpp
#include <cuda_runtime.h>
#include <cuda_bf16.h>
#include <cuda.h>
#include <stdint.h>

namespace {

constexpr int SEQ = 2048, DM = 576, FF = 4608, NQKV = 1728;

__device__ __align__(128) uint4 g_halo[128 * 384];
__device__ __align__(1024) uint4 g_wimg[8 * 18 * 1024];
__device__ __align__(128) uint4 g_stat[SEQ];
__device__ __align__(128) float g_csq[4 * NQKV];
__device__ __align__(128) float g_wsum[DM];
constexpr int FL_J = 64 * 32, FL_W = FL_J + 32;
__device__ __align__(128) unsigned int g_flag[FL_W + 32];
__device__ unsigned int g_epoch[128];
__device__ unsigned int g_claim[8];

__device__ __forceinline__ uint32_t smem_u32(const void* p) { return (uint32_t)__cvta_generic_to_shared(p); }
__device__ __forceinline__ void mbar_init(uint32_t bar, uint32_t count) {
  asm volatile("mbarrier.init.shared::cta.b64 [%0], %1;" ::"r"(bar), "r"(count) : "memory");
}
__device__ __forceinline__ void mbar_expect_tx(uint32_t bar, uint32_t bytes) {
  asm volatile("mbarrier.arrive.expect_tx.shared::cta.b64 _, [%0], %1;" ::"r"(bar), "r"(bytes) : "memory");
}
__device__ __forceinline__ void mbar_arrive(uint32_t bar) {
  asm volatile("mbarrier.arrive.shared::cta.b64 _, [%0];" ::"r"(bar) : "memory");
}
#define SPIN_LIMIT "1048576"
#define SPIN_MAX 1048576
__device__ __forceinline__ void mbar_wait(uint32_t bar, uint32_t parity) {
  asm volatile(
      "{\n.reg .pred p, c;\n.reg .u32 n;\nmov.u32 n, 0;\n"
      "WAIT:\nmbarrier.try_wait.parity.shared::cta.b64 p, [%0], %1;\n"
      "add.u32 n, n, 1;\nsetp.lt.and.u32 c, n, " SPIN_LIMIT ", !p;\n@c bra.uni WAIT;\n}"
      :
      : "r"(bar), "r"(parity)
      : "memory");
}
__device__ __forceinline__ void mbar_wait2(uint32_t a, uint32_t pa, uint32_t b, uint32_t pb) {
  asm volatile(
      "{\n.reg .pred p, q, c;\n.reg .u32 n;\nmov.u32 n, 0;\n"
      "WAIT:\nmbarrier.try_wait.parity.shared::cta.b64 p, [%0], %1;\nmbarrier.try_wait.parity.shared::cta.b64 q, [%2], %3;\n"
      "add.u32 n, n, 1;\nand.pred p, p, q;\nsetp.lt.and.u32 c, n, " SPIN_LIMIT ", !p;\n@c bra.uni WAIT;\n}"
      :
      : "r"(a), "r"(pa), "r"(b), "r"(pb)
      : "memory");
}
__device__ __forceinline__ void mbar_wait3(uint32_t a, uint32_t pa, uint32_t b, uint32_t pb, uint32_t d, uint32_t pd) {
  asm volatile(
      "{\n.reg .pred p, q, r, c;\n.reg .u32 n;\nmov.u32 n, 0;\n"
      "WAIT:\nmbarrier.try_wait.parity.shared::cta.b64 p, [%0], %1;\nmbarrier.try_wait.parity.shared::cta.b64 q, [%2], %3;\n"
      "mbarrier.try_wait.parity.shared::cta.b64 r, [%4], %5;\n"
      "add.u32 n, n, 1;\nand.pred p, p, q;\nand.pred p, p, r;\nsetp.lt.and.u32 c, n, " SPIN_LIMIT ", !p;\n@c bra.uni WAIT;\n}"
      :
      : "r"(a), "r"(pa), "r"(b), "r"(pb), "r"(d), "r"(pd)
      : "memory");
}
__device__ __forceinline__ void mbar_arrive_if(uint32_t bar, bool on) {
  asm volatile("{\n.reg .pred p;\nsetp.ne.u32 p, %1, 0;\n@p mbarrier.arrive.shared::cluster.b64 _, [%0];\n}" ::"r"(bar), "r"((uint32_t)on) : "memory");
}
__device__ __forceinline__ bool mbar_test(uint32_t bar, uint32_t parity) {
  uint32_t r;
  asm volatile("{\n.reg .pred p;\nmbarrier.test_wait.parity.shared::cta.b64 p, [%1], %2;\nselp.u32 %0, 1, 0, p;\n}"
               : "=r"(r) : "r"(bar), "r"(parity) : "memory");
  return r != 0;
}
__device__ __forceinline__ void poll_ge(const unsigned int* p, unsigned int target) {
  asm volatile(
      "{\n.reg .pred p, c;\n.reg .u32 n;\n.reg .s32 v;\nmov.u32 n, 0;\n"
      "POLL:\nld.relaxed.gpu.global.u32 v, [%0];\nsub.s32 v, v, %1;\nsetp.lt.s32 p, v, 0;\n"
      "add.u32 n, n, 1;\nsetp.lt.and.u32 c, n, " SPIN_LIMIT ", p;\n@c bra.uni POLL;\n}"
      :
      : "l"(p), "r"(target)
      : "memory");
}
__device__ __forceinline__ void signal_release(unsigned int* p, uint32_t v = 1) {
  asm volatile("red.release.gpu.global.add.u32 [%0], %1;" ::"l"(p), "r"(v) : "memory");
}
__device__ __forceinline__ void signal_relaxed(unsigned int* p, uint32_t v = 1) {
  asm volatile("red.relaxed.gpu.global.add.u32 [%0], %1;" ::"l"(p), "r"(v) : "memory");
}
__device__ __forceinline__ bool elect_one() {
  uint32_t pred;
  asm volatile("{\n.reg .pred p;\nelect.sync _|p, 0xffffffff;\nselp.u32 %0, 1, 0, p;\n}" : "=r"(pred));
  return pred != 0;
}
__device__ __forceinline__ void tma_load_2d(uint32_t dst, const CUtensorMap* map, uint32_t bar, int c0, int c1) {
  asm volatile(
      "cp.async.bulk.tensor.2d.shared::cluster.global.mbarrier::complete_tx::bytes [%0], [%1, {%3, %4}], [%2];" ::"r"(dst),
      "l"(map), "r"(bar), "r"(c0), "r"(c1)
      : "memory");
}
__device__ __forceinline__ void tma_load_3d(uint32_t dst, const CUtensorMap* map, uint32_t bar, int c0, int c1, int c2) {
  asm volatile(
      "cp.async.bulk.tensor.3d.shared::cluster.global.mbarrier::complete_tx::bytes [%0], [%1, {%3, %4, %5}], [%2];" ::"r"(dst),
      "l"(map), "r"(bar), "r"(c0), "r"(c1), "r"(c2)
      : "memory");
}
__device__ __forceinline__ void tma_load_3d_mc(uint32_t dst, const CUtensorMap* map, uint32_t bar, int c0, int c1, int c2) {
  asm volatile(
      "cp.async.bulk.tensor.3d.shared::cluster.global.mbarrier::complete_tx::bytes.multicast::cluster [%0], [%1, {%3, "
      "%4, %5}], [%2], %6;" ::"r"(dst),
      "l"(map), "r"(bar), "r"(c0), "r"(c1), "r"(c2), "h"((uint16_t)3)
      : "memory");
}
__device__ __forceinline__ void st_async_u4(uint32_t dst, uint32_t bar, uint32_t a, uint32_t b, uint32_t c, uint32_t d) {
  asm volatile("st.async.weak.shared::cluster.mbarrier::complete_tx::bytes.v4.b32 [%0], {%2, %3, %4, %5}, [%1];" ::"r"(dst),
               "r"(bar), "r"(a), "r"(b), "r"(c), "r"(d)
               : "memory");
}
__device__ __forceinline__ void tma_reduce_3d(const CUtensorMap* map, uint32_t src, int c0, int c1, int c2) {
  asm volatile("cp.reduce.async.bulk.tensor.3d.global.shared::cta.add.tile.bulk_group [%0, {%2, %3, %4}], [%1];" ::"l"(map),
               "r"(src), "r"(c0), "r"(c1), "r"(c2)
               : "memory");
}
__device__ __forceinline__ void tma_store_3d(const CUtensorMap* map, uint32_t src, int c0, int c1, int c2) {
  asm volatile("cp.async.bulk.tensor.3d.global.shared::cta.tile.bulk_group [%0, {%2, %3, %4}], [%1];" ::"l"(map), "r"(src),
               "r"(c0), "r"(c1), "r"(c2)
               : "memory");
}
__device__ __forceinline__ void tma_prefetch_2d(const CUtensorMap* map, int c0, int c1) {
  asm volatile("cp.async.bulk.prefetch.tensor.2d.L2.global.tile [%0, {%1, %2}];" ::"l"(map), "r"(c0), "r"(c1) : "memory");
}
__device__ __forceinline__ void prefetch_map(const CUtensorMap* map) {
  asm volatile("prefetch.tensormap [%0];" ::"l"(map) : "memory");
}
__device__ __forceinline__ void wgmma_fence() { asm volatile("wgmma.fence.sync.aligned;" ::: "memory"); }
__device__ __forceinline__ void wgmma_commit() { asm volatile("wgmma.commit_group.sync.aligned;" ::: "memory"); }
template <int N>
__device__ __forceinline__ void wgmma_wait() {
  asm volatile("wgmma.wait_group.sync.aligned %0;" ::"n"(N) : "memory");
}
__device__ __forceinline__ void named_bar_sync(int id, int nthreads) {
  asm volatile("bar.sync %0, %1;" ::"r"(id), "r"(nthreads) : "memory");
}
__device__ __forceinline__ void cluster_arrive_relaxed() { asm volatile("barrier.cluster.arrive.relaxed.aligned;" ::: "memory"); }
__device__ __forceinline__ void cluster_wait() { asm volatile("barrier.cluster.wait.acquire.aligned;" ::: "memory"); }
__device__ __forceinline__ uint32_t mapa(uint32_t addr, uint32_t rank) {
  uint32_t r;
  asm volatile("mapa.shared::cluster.u32 %0, %1, %2;" : "=r"(r) : "r"(addr), "r"(rank));
  return r;
}
__device__ __forceinline__ uint64_t desc_from_lo(uint32_t lo) { return (uint64_t)lo | (0x40000040ull << 32); }
__device__ __forceinline__ uint64_t desc_sbo(uint32_t lo, uint32_t sbo) { return (uint64_t)lo | ((0x40000000ull | (sbo >> 4)) << 32); }
__device__ __forceinline__ uint32_t desc_lo_a(uint32_t addr) { return ((addr & 0x3FFFF) >> 4) | (1u << 16); }
__device__ __forceinline__ uint32_t desc_lo_b(uint32_t addr, uint32_t lbo_bytes) { return ((addr & 0x3FFFF) >> 4) | ((lbo_bytes >> 4) << 16); }
__device__ __forceinline__ uint32_t pack_bf16(float lo, float hi) {
  __nv_bfloat162 v = __floats2bfloat162_rn(lo, hi);
  return *reinterpret_cast<uint32_t*>(&v);
}
__device__ __forceinline__ float bf16r(float x) { return __uint_as_float(pack_bf16(0.f, x)); }
__device__ __forceinline__ float bf_lo(uint32_t u) { return __uint_as_float(u << 16); }
__device__ __forceinline__ float bf_hi(uint32_t u) { return __uint_as_float(u & 0xFFFF0000u); }
__device__ __forceinline__ uint4 lds_u4(uint32_t addr) {
  uint4 v;
  asm volatile("ld.shared.v4.b32 {%0, %1, %2, %3}, [%4];" : "=r"(v.x), "=r"(v.y), "=r"(v.z), "=r"(v.w) : "r"(addr) : "memory");
  return v;
}
__device__ __forceinline__ float2 lds_f2(uint32_t addr) {
  float2 v;
  asm volatile("ld.shared.v2.f32 {%0, %1}, [%2];" : "=f"(v.x), "=f"(v.y) : "r"(addr) : "memory");
  return v;
}
__device__ __forceinline__ void sts_f2(uint32_t addr, float a, float b) {
  asm volatile("st.shared.v2.f32 [%0], {%1, %2};" ::"r"(addr), "f"(a), "f"(b) : "memory");
}
__device__ __forceinline__ void sts_u4(uint32_t addr, uint32_t a, uint32_t b, uint32_t c, uint32_t d) {
  asm volatile("st.shared.v4.b32 [%0], {%1, %2, %3, %4};" ::"r"(addr), "r"(a), "r"(b), "r"(c), "r"(d) : "memory");
}
__device__ __forceinline__ void sts_u32(uint32_t addr, uint32_t v) { asm volatile("st.shared.b32 [%0], %1;" ::"r"(addr), "r"(v) : "memory"); }
__device__ __forceinline__ uint32_t lds_u32(uint32_t addr) {
  uint32_t v;
  asm volatile("ld.shared.b32 %0, [%1];" : "=r"(v) : "r"(addr) : "memory");
  return v;
}
__device__ __forceinline__ uint4 ldg_u4(const void* p, bool on = true) {
  uint4 v = make_uint4(0u, 0u, 0u, 0u);
  asm volatile("{\n.reg .pred p;\nsetp.ne.u32 p, %5, 0;\n@p ld.global.nc.L1::no_allocate.v4.b32 {%0, %1, %2, %3}, [%4];\n}"
               : "+r"(v.x), "+r"(v.y), "+r"(v.z), "+r"(v.w) : "l"(p), "r"((uint32_t)on) : "memory");
  return v;
}
__device__ __forceinline__ float4 ldg_cg_f4(const void* p) {
  float4 v;
  asm volatile("ld.global.cg.v4.f32 {%0, %1, %2, %3}, [%4];" : "=f"(v.x), "=f"(v.y), "=f"(v.z), "=f"(v.w) : "l"(p) : "memory");
  return v;
}
__device__ __forceinline__ void st_tagged(void* p, uint32_t a, uint32_t b, uint32_t c, uint32_t tag) {
  asm volatile("{\n.reg .b64 l, h;\n.reg .b128 v;\nmov.b64 l, {%1, %2};\nmov.b64 h, {%3, %4};\nmov.b128 v, {l, h};\n"
               "st.relaxed.gpu.global.b128 [%0], v;\n}" ::"l"(p), "r"(a), "r"(b), "r"(c), "r"(tag) : "memory");
}
__device__ __forceinline__ void st_tagged_any(uint64_t p, uint32_t a, uint32_t b, uint32_t c, uint32_t tag) {
  asm volatile("{\n.reg .b64 l, h;\n.reg .b128 v;\nmov.b64 l, {%1, %2};\nmov.b64 h, {%3, %4};\nmov.b128 v, {l, h};\n"
               "st.relaxed.gpu.b128 [%0], v;\n}" ::"l"(p), "r"(a), "r"(b), "r"(c), "r"(tag) : "memory");
}
__device__ __forceinline__ uint4 ld_tagged(const void* p) {
  uint4 r;
  asm volatile("{\n.reg .b64 l, h;\n.reg .b128 v;\nld.relaxed.gpu.global.b128 v, [%4];\nmov.b128 {l, h}, v;\n"
               "mov.b64 {%0, %1}, l;\nmov.b64 {%2, %3}, h;\n}" : "=r"(r.x), "=r"(r.y), "=r"(r.z), "=r"(r.w) : "l"(p) : "memory");
  return r;
}
__device__ __forceinline__ void cp_async16(uint32_t dst, const void* src) {
  asm volatile("cp.async.cg.shared.global [%0], [%1], 16;" ::"r"(dst), "l"(src) : "memory");
}
__device__ __forceinline__ void cp_async_arrive(uint32_t bar) {
  asm volatile("cp.async.mbarrier.arrive.shared::cta.b64 [%0];" ::"r"(bar) : "memory");
}
__device__ __forceinline__ void bulk_store(void* gdst, uint32_t src, uint32_t bytes) {
  asm volatile("cp.async.bulk.global.shared::cta.bulk_group [%0], [%1], %2;" ::"l"(gdst), "r"(src), "r"(bytes) : "memory");
}
__device__ __forceinline__ void bulk_load(uint32_t dst, const void* gsrc, uint32_t bytes, uint32_t bar) {
  asm volatile("cp.async.bulk.shared::cluster.global.mbarrier::complete_tx::bytes [%0], [%1], %2, [%3];" ::"r"(dst), "l"(gsrc),
               "r"(bytes), "r"(bar)
               : "memory");
}
__device__ __forceinline__ void bulk_commit() { asm volatile("cp.async.bulk.commit_group;" ::: "memory"); }
template <int N>
__device__ __forceinline__ void bulk_wait() { asm volatile("cp.async.bulk.wait_group %0;" ::"n"(N) : "memory"); }
__device__ __forceinline__ void stsm_x4(uint32_t addr, uint32_t a, uint32_t b, uint32_t c, uint32_t d) {
  asm volatile("stmatrix.sync.aligned.m8n8.x4.shared.b16 [%0], {%1, %2, %3, %4};" ::"r"(addr), "r"(a), "r"(b), "r"(c), "r"(d) : "memory");
}
__device__ __forceinline__ uint32_t movm(uint32_t a) {
  uint32_t d;
  asm volatile("movmatrix.sync.aligned.m8n8.trans.b16 %0, %1;" : "=r"(d) : "r"(a));
  return d;
}
__device__ __forceinline__ void mma_16816(float (&d)[4], uint32_t a0, uint32_t a1, uint32_t a2, uint32_t a3, uint32_t b0, uint32_t b1) {
  asm volatile("mma.sync.aligned.m16n8k16.row.col.f32.bf16.bf16.f32 {%0, %1, %2, %3}, {%4, %5, %6, %7}, {%8, %9}, {%0, %1, %2, %3};"
               : "+f"(d[0]), "+f"(d[1]), "+f"(d[2]), "+f"(d[3]) : "r"(a0), "r"(a1), "r"(a2), "r"(a3), "r"(b0), "r"(b1));
}
__device__ __forceinline__ void mma_16816_z(float (&d)[4], uint32_t a0, uint32_t a1, uint32_t a2, uint32_t a3, uint32_t b0, uint32_t b1) {
  asm volatile("mma.sync.aligned.m16n8k16.row.col.f32.bf16.bf16.f32 {%0, %1, %2, %3}, {%4, %5, %6, %7}, {%8, %9}, {%10, %10, %10, %10};"
               : "=f"(d[0]), "=f"(d[1]), "=f"(d[2]), "=f"(d[3]) : "r"(a0), "r"(a1), "r"(a2), "r"(a3), "r"(b0), "r"(b1), "f"(0.f));
}
__device__ __forceinline__ void mma_1688(float (&d)[4], uint32_t a0, uint32_t a1, uint32_t b0) {
  asm volatile("mma.sync.aligned.m16n8k8.row.col.f32.bf16.bf16.f32 {%0, %1, %2, %3}, {%4, %5}, {%6}, {%7, %7, %7, %7};"
               : "=f"(d[0]), "=f"(d[1]), "=f"(d[2]), "=f"(d[3]) : "r"(a0), "r"(a1), "r"(b0), "f"(0.f));
}
__device__ __forceinline__ void fence_proxy_async() { asm volatile("fence.proxy.async.shared::cta;" ::: "memory"); }

template<int N> __device__ __forceinline__ void wgmma_ss(float (&d)[N/2], uint64_t descA, uint64_t descB, int scaleD);
template<int N> __device__ __forceinline__ void wgmma_rs(float (&d)[N/2], uint32_t a0, uint32_t a1, uint32_t a2, uint32_t a3, uint64_t descB, int scaleD);
template<> __device__ __forceinline__ void wgmma_ss<128>(float (&d)[64], uint64_t descA, uint64_t descB, int scaleD) {
  asm volatile("{\n.reg .pred p;\nsetp.ne.b32 p, %66, 0;\n"
    "wgmma.mma_async.sync.aligned.m64n128k16.f32.bf16.bf16 {%0, %1, %2, %3, %4, %5, %6, %7, %8, %9, %10, %11, %12, %13, %14, %15, %16, %17, %18, %19, %20, %21, %22, %23, %24, %25, %26, %27, %28, %29, %30, %31, %32, %33, %34, %35, %36, %37, %38, %39, %40, %41, %42, %43, %44, %45, %46, %47, %48, %49, %50, %51, %52, %53, %54, %55, %56, %57, %58, %59, %60, %61, %62, %63}, %64, %65, p, 1, 1, 0, 1;\n}\n"
    : "+f"(d[0]), "+f"(d[1]), "+f"(d[2]), "+f"(d[3]), "+f"(d[4]), "+f"(d[5]), "+f"(d[6]), "+f"(d[7]), "+f"(d[8]), "+f"(d[9]), "+f"(d[10]), "+f"(d[11]), "+f"(d[12]), "+f"(d[13]), "+f"(d[14]), "+f"(d[15]), "+f"(d[16]), "+f"(d[17]), "+f"(d[18]), "+f"(d[19]), "+f"(d[20]), "+f"(d[21]), "+f"(d[22]), "+f"(d[23]), "+f"(d[24]), "+f"(d[25]), "+f"(d[26]), "+f"(d[27]), "+f"(d[28]), "+f"(d[29]), "+f"(d[30]), "+f"(d[31]), "+f"(d[32]), "+f"(d[33]), "+f"(d[34]), "+f"(d[35]), "+f"(d[36]), "+f"(d[37]), "+f"(d[38]), "+f"(d[39]), "+f"(d[40]), "+f"(d[41]), "+f"(d[42]), "+f"(d[43]), "+f"(d[44]), "+f"(d[45]), "+f"(d[46]), "+f"(d[47]), "+f"(d[48]), "+f"(d[49]), "+f"(d[50]), "+f"(d[51]), "+f"(d[52]), "+f"(d[53]), "+f"(d[54]), "+f"(d[55]), "+f"(d[56]), "+f"(d[57]), "+f"(d[58]), "+f"(d[59]), "+f"(d[60]), "+f"(d[61]), "+f"(d[62]), "+f"(d[63])
    : "l"(descA), "l"(descB), "r"(scaleD));
}
template<> __device__ __forceinline__ void wgmma_ss<216>(float (&d)[108], uint64_t descA, uint64_t descB, int scaleD) {
  asm volatile("{\n.reg .pred p;\nsetp.ne.b32 p, %110, 0;\n"
    "wgmma.mma_async.sync.aligned.m64n216k16.f32.bf16.bf16 {%0, %1, %2, %3, %4, %5, %6, %7, %8, %9, %10, %11, %12, %13, %14, %15, %16, %17, %18, %19, %20, %21, %22, %23, %24, %25, %26, %27, %28, %29, %30, %31, %32, %33, %34, %35, %36, %37, %38, %39, %40, %41, %42, %43, %44, %45, %46, %47, %48, %49, %50, %51, %52, %53, %54, %55, %56, %57, %58, %59, %60, %61, %62, %63, %64, %65, %66, %67, %68, %69, %70, %71, %72, %73, %74, %75, %76, %77, %78, %79, %80, %81, %82, %83, %84, %85, %86, %87, %88, %89, %90, %91, %92, %93, %94, %95, %96, %97, %98, %99, %100, %101, %102, %103, %104, %105, %106, %107}, %108, %109, p, 1, 1, 0, 1;\n}\n"
    : "+f"(d[0]), "+f"(d[1]), "+f"(d[2]), "+f"(d[3]), "+f"(d[4]), "+f"(d[5]), "+f"(d[6]), "+f"(d[7]), "+f"(d[8]), "+f"(d[9]), "+f"(d[10]), "+f"(d[11]), "+f"(d[12]), "+f"(d[13]), "+f"(d[14]), "+f"(d[15]), "+f"(d[16]), "+f"(d[17]), "+f"(d[18]), "+f"(d[19]), "+f"(d[20]), "+f"(d[21]), "+f"(d[22]), "+f"(d[23]), "+f"(d[24]), "+f"(d[25]), "+f"(d[26]), "+f"(d[27]), "+f"(d[28]), "+f"(d[29]), "+f"(d[30]), "+f"(d[31]), "+f"(d[32]), "+f"(d[33]), "+f"(d[34]), "+f"(d[35]), "+f"(d[36]), "+f"(d[37]), "+f"(d[38]), "+f"(d[39]), "+f"(d[40]), "+f"(d[41]), "+f"(d[42]), "+f"(d[43]), "+f"(d[44]), "+f"(d[45]), "+f"(d[46]), "+f"(d[47]), "+f"(d[48]), "+f"(d[49]), "+f"(d[50]), "+f"(d[51]), "+f"(d[52]), "+f"(d[53]), "+f"(d[54]), "+f"(d[55]), "+f"(d[56]), "+f"(d[57]), "+f"(d[58]), "+f"(d[59]), "+f"(d[60]), "+f"(d[61]), "+f"(d[62]), "+f"(d[63]), "+f"(d[64]), "+f"(d[65]), "+f"(d[66]), "+f"(d[67]), "+f"(d[68]), "+f"(d[69]), "+f"(d[70]), "+f"(d[71]), "+f"(d[72]), "+f"(d[73]), "+f"(d[74]), "+f"(d[75]), "+f"(d[76]), "+f"(d[77]), "+f"(d[78]), "+f"(d[79]), "+f"(d[80]), "+f"(d[81]), "+f"(d[82]), "+f"(d[83]), "+f"(d[84]), "+f"(d[85]), "+f"(d[86]), "+f"(d[87]), "+f"(d[88]), "+f"(d[89]), "+f"(d[90]), "+f"(d[91]), "+f"(d[92]), "+f"(d[93]), "+f"(d[94]), "+f"(d[95]), "+f"(d[96]), "+f"(d[97]), "+f"(d[98]), "+f"(d[99]), "+f"(d[100]), "+f"(d[101]), "+f"(d[102]), "+f"(d[103]), "+f"(d[104]), "+f"(d[105]), "+f"(d[106]), "+f"(d[107])
    : "l"(descA), "l"(descB), "r"(scaleD));
}
template<> __device__ __forceinline__ void wgmma_rs<64>(float (&d)[32], uint32_t a0, uint32_t a1, uint32_t a2, uint32_t a3, uint64_t descB, int scaleD) {
  asm volatile("{\n.reg .pred p;\nsetp.ne.b32 p, %37, 0;\n"
    "wgmma.mma_async.sync.aligned.m64n64k16.f32.bf16.bf16 {%0, %1, %2, %3, %4, %5, %6, %7, %8, %9, %10, %11, %12, %13, %14, %15, %16, %17, %18, %19, %20, %21, %22, %23, %24, %25, %26, %27, %28, %29, %30, %31}, {%32, %33, %34, %35}, %36, p, 1, 1, 1;\n}\n"
    : "+f"(d[0]), "+f"(d[1]), "+f"(d[2]), "+f"(d[3]), "+f"(d[4]), "+f"(d[5]), "+f"(d[6]), "+f"(d[7]), "+f"(d[8]), "+f"(d[9]), "+f"(d[10]), "+f"(d[11]), "+f"(d[12]), "+f"(d[13]), "+f"(d[14]), "+f"(d[15]), "+f"(d[16]), "+f"(d[17]), "+f"(d[18]), "+f"(d[19]), "+f"(d[20]), "+f"(d[21]), "+f"(d[22]), "+f"(d[23]), "+f"(d[24]), "+f"(d[25]), "+f"(d[26]), "+f"(d[27]), "+f"(d[28]), "+f"(d[29]), "+f"(d[30]), "+f"(d[31])
    : "r"(a0), "r"(a1), "r"(a2), "r"(a3), "l"(descB), "r"(scaleD));
}
template<> __device__ __forceinline__ void wgmma_rs<216>(float (&d)[108], uint32_t a0, uint32_t a1, uint32_t a2, uint32_t a3, uint64_t descB, int scaleD) {
  asm volatile("{\n.reg .pred p;\nsetp.ne.b32 p, %113, 0;\n"
    "wgmma.mma_async.sync.aligned.m64n216k16.f32.bf16.bf16 {%0, %1, %2, %3, %4, %5, %6, %7, %8, %9, %10, %11, %12, %13, %14, %15, %16, %17, %18, %19, %20, %21, %22, %23, %24, %25, %26, %27, %28, %29, %30, %31, %32, %33, %34, %35, %36, %37, %38, %39, %40, %41, %42, %43, %44, %45, %46, %47, %48, %49, %50, %51, %52, %53, %54, %55, %56, %57, %58, %59, %60, %61, %62, %63, %64, %65, %66, %67, %68, %69, %70, %71, %72, %73, %74, %75, %76, %77, %78, %79, %80, %81, %82, %83, %84, %85, %86, %87, %88, %89, %90, %91, %92, %93, %94, %95, %96, %97, %98, %99, %100, %101, %102, %103, %104, %105, %106, %107}, {%108, %109, %110, %111}, %112, p, 1, 1, 1;\n}\n"
    : "+f"(d[0]), "+f"(d[1]), "+f"(d[2]), "+f"(d[3]), "+f"(d[4]), "+f"(d[5]), "+f"(d[6]), "+f"(d[7]), "+f"(d[8]), "+f"(d[9]), "+f"(d[10]), "+f"(d[11]), "+f"(d[12]), "+f"(d[13]), "+f"(d[14]), "+f"(d[15]), "+f"(d[16]), "+f"(d[17]), "+f"(d[18]), "+f"(d[19]), "+f"(d[20]), "+f"(d[21]), "+f"(d[22]), "+f"(d[23]), "+f"(d[24]), "+f"(d[25]), "+f"(d[26]), "+f"(d[27]), "+f"(d[28]), "+f"(d[29]), "+f"(d[30]), "+f"(d[31]), "+f"(d[32]), "+f"(d[33]), "+f"(d[34]), "+f"(d[35]), "+f"(d[36]), "+f"(d[37]), "+f"(d[38]), "+f"(d[39]), "+f"(d[40]), "+f"(d[41]), "+f"(d[42]), "+f"(d[43]), "+f"(d[44]), "+f"(d[45]), "+f"(d[46]), "+f"(d[47]), "+f"(d[48]), "+f"(d[49]), "+f"(d[50]), "+f"(d[51]), "+f"(d[52]), "+f"(d[53]), "+f"(d[54]), "+f"(d[55]), "+f"(d[56]), "+f"(d[57]), "+f"(d[58]), "+f"(d[59]), "+f"(d[60]), "+f"(d[61]), "+f"(d[62]), "+f"(d[63]), "+f"(d[64]), "+f"(d[65]), "+f"(d[66]), "+f"(d[67]), "+f"(d[68]), "+f"(d[69]), "+f"(d[70]), "+f"(d[71]), "+f"(d[72]), "+f"(d[73]), "+f"(d[74]), "+f"(d[75]), "+f"(d[76]), "+f"(d[77]), "+f"(d[78]), "+f"(d[79]), "+f"(d[80]), "+f"(d[81]), "+f"(d[82]), "+f"(d[83]), "+f"(d[84]), "+f"(d[85]), "+f"(d[86]), "+f"(d[87]), "+f"(d[88]), "+f"(d[89]), "+f"(d[90]), "+f"(d[91]), "+f"(d[92]), "+f"(d[93]), "+f"(d[94]), "+f"(d[95]), "+f"(d[96]), "+f"(d[97]), "+f"(d[98]), "+f"(d[99]), "+f"(d[100]), "+f"(d[101]), "+f"(d[102]), "+f"(d[103]), "+f"(d[104]), "+f"(d[105]), "+f"(d[106]), "+f"(d[107])
    : "r"(a0), "r"(a1), "r"(a2), "r"(a3), "l"(descB), "r"(scaleD));
}

constexpr int TILE = 8192, HALF = 9 * TILE;
constexpr int SLOT = 16384;
constexpr int RING = 2 * HALF;
constexpr int OVF = RING + 5 * SLOT;
constexpr int TAB = OVF + 1024;
constexpr int BARS = TAB + 1024;
constexpr int SMEM_BYTES = BARS + 1024;
constexpr int WOA = 9216;
constexpr int B_FULL = BARS, B_FX = BARS + 56, B_AUX = BARS + 200, B_NB = BARS + 208, B_ROLE = BARS + 272, B_S1 = BARS + 280,
              B_ST = BARS + 288, B_EMPTY = BARS + 432, B_J = BARS + 488, B_XF = BARS + 496,
              B_QK = BARS + 504, B_RX = BARS + 512, B_SR = BARS + 528, B_OX = BARS + 536, B_HP = BARS + 552;
constexpr int S_ROLE = BARS + 568, S_EP = BARS + 572, S_WS = BARS + 576;

template <int V>
struct IC {
  static constexpr int value = V;
};
struct Maps {
  CUtensorMap x0, r, wq, wo, wg, wu, wd;
};

#define TA0(i)
#define TA(i)
#define TS(i)
#define TR(i)

__device__ __forceinline__ int tid_now() {
  int t;
  asm volatile("mov.u32 %0, %%tid.x;" : "=r"(t));
  return t;
}
__device__ __forceinline__ float quad_sum(float v) {
  v += __shfl_xor_sync(0xffffffffu, v, 1);
  return v + __shfl_xor_sync(0xffffffffu, v, 2);
}
__device__ __forceinline__ float inv_sd(float var) {
  float s, r;
  asm("sqrt.approx.ftz.f32 %0, %1;" : "=f"(s) : "f"(bf16r(bf16r(fmaxf(var, 0.f)) + 1e-5f)));
  asm("rcp.approx.ftz.f32 %0, %1;" : "=f"(r) : "f"(bf16r(s)));
  return r;
}
__device__ __forceinline__ float sum8(const uint4& v) {
  return ((bf_lo(v.x) + bf_hi(v.x)) + (bf_lo(v.y) + bf_hi(v.y))) + ((bf_lo(v.z) + bf_hi(v.z)) + (bf_lo(v.w) + bf_hi(v.w)));
}
__device__ __forceinline__ void warp_arrive(uint32_t bar) {
  __syncwarp();
  if ((tid_now() & 31) == 0) mbar_arrive(bar);
}
__device__ __forceinline__ void release_slot(uint32_t sb, int p, bool on = true) {
  asm volatile("{\n.reg .pred p;\nsetp.eq.u32 p, %1, 0;\n@p mbarrier.arrive.shared::cta.b64 _, [%0];\n}" ::"r"(sb + B_EMPTY + 8 * p),
               "r"((tid_now() & 31) | (on ? 0 : 1))
               : "memory");
}
__device__ __forceinline__ uint32_t stage_addr(uint32_t sb) {
  const int tid = tid_now(), lane = tid & 31;
  return sb + (tid >> 7) * HALF + ((tid >> 5) & 3) * 2048 + (lane & 15) * 128 + (((lane >> 4) ^ (lane & 7)) << 4);
}
__device__ __forceinline__ void stage_done(uint32_t sb, int a, int n) {
    __syncwarp();
  const int tid = tid_now();
  if ((tid & 31) < n) mbar_arrive(sb + B_ST + 72 * (tid >> 7) + 8 * (a + (tid & 31)));
}
template <int I0 = 0, int I1 = 4>
__device__ __forceinline__ void stage_tile(const float (&acc)[32], float m0, float c0, float m1, float c1, uint32_t sb, int a, int b, int n) {
  const uint32_t ad = stage_addr(sb) + a * TILE;
#pragma unroll
  for (int i = I0; i < I1; ++i)
    stsm_x4(ad ^ (i << 5), pack_bf16(fmaf(acc[8 * i], m0, c0), fmaf(acc[8 * i + 1], m0, c0)),
            pack_bf16(fmaf(acc[8 * i + 2], m1, c1), fmaf(acc[8 * i + 3], m1, c1)),
            pack_bf16(fmaf(acc[8 * i + 4], m0, c0), fmaf(acc[8 * i + 5], m0, c0)),
            pack_bf16(fmaf(acc[8 * i + 6], m1, c1), fmaf(acc[8 * i + 7], m1, c1)));
  if (n) stage_done(sb, b, n);
}

#define NLAYERS 2
#define X_EARLY 2
#define X_SCHED 0x1111111ull
#define PACE 2800
#define X_PF 0
#define DN_LATE 0
#define ST_END 5
#define GU_PF0 16
#define GU_PFN 16
#define R0_N 0
#define R1_N 2
#define PACE_R 1400
#define PACE0 4200
#define IMG 1
#define GU_PRE 1
#define Q_H 8
#define LAZY 2
#define Q_ST0 7
#define Q_ST1 6

__global__ void __cluster_dims__(2, 1, 1) __launch_bounds__(384, 1)
mega_kernel(const __grid_constant__ Maps mp, const __nv_bfloat16* __restrict__ x0, const __nv_bfloat16* __restrict__ wqkv,
            const __nv_bfloat16* __restrict__ wo, __nv_bfloat16* __restrict__ out, int small_gpc) {
  extern __shared__ __align__(1024) uint8_t smem[];
  const uint32_t sb = smem_u32(smem);
  const uint32_t rank = blockIdx.x & 1;
  const int warp = __shfl_sync(0xffffffffu, threadIdx.x >> 5, 0);
  TA0(63);
  uint32_t claim = 0, ep1 = 0;
  if (warp == 8) {
    if (threadIdx.x == 256 && rank == 0) {
      uint32_t tp;
      asm volatile("mov.u32 %0, %%smid;" : "=r"(tp));
      tp >>= 1;
      uint32_t pr = !small_gpc || tp < 32 ? tp & 7 : tp < 60 ? 1 + (tp - 32) % 7 : 0;
#pragma unroll 1
      for (int i = 0; i < 8; ++i, pr = (pr + 1) & 7) {
        claim = atomicAdd(&g_claim[pr], 1u);
        if (claim < 8) break;
      }
      claim = ((pr >> 2) * 8 + (claim & 7)) * 4 + (pr & 3);
    }
  } else {
    if (warp > 8) ep1 = g_epoch[blockIdx.x] + 1;
    if (elect_one()) {
      const uint32_t b0 = sb + BARS + 48 * (warp - (warp > 8));
      if (warp < 11) {
#pragma unroll
        for (int i = 0; i < 6; ++i) mbar_init(b0 + 8 * i, warp < 6 ? 1 : warp < 10 ? 4 : 8);
        if (warp == 5) mbar_expect_tx(sb + B_ROLE, 4);
      } else {
#pragma unroll
        for (int i = 0; i < 11; ++i) mbar_init(b0 + 8 * i, i < 3 ? 8 : i < 6 ? 4 : i < 7 ? 2 : 1);
      }
      asm volatile("fence.mbarrier_init.release.cluster;" ::: "memory");
      if (warp == 9) prefetch_map(&mp.x0);
      if (warp == 10) prefetch_map(&mp.wq);
    }
  }
  __syncwarp();
  cluster_arrive_relaxed();
  TA0(2);

  if (warp >= 8) {
    cluster_wait();
    if (threadIdx.x == 256 && rank == 0) {
#pragma unroll
      for (int r = 0; r < 2; ++r)
        asm volatile("st.async.weak.shared::cluster.mbarrier::complete_tx::bytes.u32 [%0], %1, [%2];" ::"r"(mapa(sb + S_ROLE, r)),
                     "r"(claim), "r"(mapa(sb + B_ROLE, r))
                     : "memory");
    }
    __syncwarp();
    asm volatile("setmaxnreg.dec.sync.aligned.u32 24;");
    mbar_wait(sb + B_ROLE, 0);
    const int role = __shfl_sync(0xffffffffu, lds_u32(sb + S_ROLE), 0);
    const int j = (role & 3) * 2 + rank, rb = role >> 2;
    ep1 = __shfl_sync(0xffffffffu, ep1, 0);
    TA0(59);
    auto load_wq = [&](uint32_t dst, uint32_t bar, int s) {
      const int lane = tid_now() & 31;
      const __nv_bfloat16* src = wqkv + (32 * s + lane) * NQKV + 72 * j + (rank ? 0 : 64);
      if (elect_one()) tma_load_3d(dst, &mp.wq, bar, 72 * j + 8 * rank, 32 * s, 0);
#pragma unroll
      for (int c = 0; c < 3; ++c) cp_async16(dst + 12288 + lane * 128 + ((c ^ (lane & 7)) << 4), src + c * 576);
      cp_async_arrive(bar);
      __syncwarp();
      if (elect_one()) mbar_expect_tx(bar, 12288);
    };
    if (warp == 8) {
      int p = 2;
      uint32_t ph = 1;
      const int f0 = j * 576;
      int xi = X_EARLY;
#pragma unroll 1
      for (int L = 0; L < NLAYERS; ++L) {
#pragma unroll 1
        for (int s = 0; s < 18; ++s) {
          const uint32_t bar = sb + B_FULL + 8 * p;
          mbar_wait(bar + (B_EMPTY - B_FULL), ph);
          TR(s);
          if (L == 0 || !IMG) {
            load_wq(sb + RING + p * SLOT, bar, s);
            if (L == 0 && elect_one()) {
#pragma unroll 1
              for (int e = (X_SCHED >> (2 * s)) & 3; e > 0; --e, ++xi)
                tma_load_3d_mc(sb + rank * HALF + xi * TILE, &mp.x0, sb + B_FX + 72 * rank + 8 * xi, xi * 64, rb * 64 + rank * 32, 0);
              const int u = (s - GU_PF0) * 8 + (rb >> 1);
              if (s >= GU_PF0 && u < GU_PFN) tma_prefetch_2d((rb & 1) ? &mp.wu : &mp.wg, f0 + 64 * (u % 3), 64 * (u / 3));
            }
          } else if (elect_one()) {
            bulk_load(sb + RING + p * SLOT, g_wimg + (j * 18 + s) * 1024, SLOT, bar);
            mbar_expect_tx(bar, SLOT);
          }
          if (++p == 5) p = 0;
          if (p == 2) ph ^= 1;
        }
#pragma unroll 1
        for (int s = 0; s < 5; ++s) {
          const int cx = s ? 64 * (2 * s - 1 + rank) : 0;
          mbar_wait(sb + B_EMPTY + 8 * s, ph);
          if (elect_one()) {
            if (s) tma_load_2d(sb + RING + (2 * s - 1) * WOA, &mp.wo, sb + B_FULL + 8 * s, cx, 72 * j);
            tma_load_2d(sb + RING + 2 * s * WOA, &mp.wo, sb + B_FULL + 8 * s, cx, 72 * (s ? j ^ 1 : j));
            mbar_expect_tx(sb + B_FULL + 8 * s, s ? 2 * WOA : WOA);
          }
          if (s == 1) ph ^= 1;
        }
        {
          int cx = f0, cy = 0;
#pragma unroll 1
          for (int n = 0; n < 81; ++n) {
            const uint32_t dst = sb + RING + p * SLOT, bar = sb + B_FULL + 8 * p;
            if (n == (rank ? R1_N : R0_N)) {
              mbar_wait(sb + B_ST + 72 + 8, 0);
              fence_proxy_async();
              if (elect_one()) tma_reduce_3d(&mp.r, sb + HALF + (1 + rank) * TILE, 64 + 64 * rank, rb * 64 + 32, 0);
              bulk_commit();
              if (!rank) {
                bulk_wait<0>();
                asm volatile("bar.arrive 8, 64;" ::: "memory");
              }
              mbar_wait(sb + B_ST + 8, 0);
              fence_proxy_async();
              if (elect_one()) tma_reduce_3d(&mp.r, sb + (1 + rank) * TILE, 64 + 64 * rank, rb * 64, 0);
              bulk_commit();
            }
            mbar_wait(bar + (B_EMPTY - B_FULL), ph);
            if (elect_one()) tma_load_2d(dst, &mp.wg, bar, cx, cy);
            if (elect_one()) tma_load_2d(dst + 8192, &mp.wu, bar, cx, cy);
            if (elect_one()) mbar_expect_tx(bar, 16384);
            if (n == (rank ? R1_N : R0_N)) {
              bulk_wait<0>();
              if (rank) asm volatile("bar.arrive 8, 64;" ::: "memory");
              asm volatile("bar.arrive 7, 64;" ::: "memory");
            }
            if (n < 26) {
              cx += 64;
              if (cx == f0 + 192) {
                cx = f0;
                cy += 64;
              }
            } else if ((cy += 64) == 576) {
              cy = 0;
              cx += 64;
            }
            if (++p == 5) p = 0;
            if (p == 2) ph ^= 1;
          }
        }
        {
          int cx = 0, cy = f0;
#pragma unroll 1
          for (int n = 35; n > -6; --n) {
            const uint32_t dst = p < 5 ? sb + RING + p * SLOT : sb + 2 * TILE + p * TILE, bar = sb + B_FULL + 8 * p;
            mbar_wait(bar + (B_EMPTY - B_FULL), ph);
            if (elect_one()) tma_load_2d(dst, &mp.wd, bar, cx, cy);
            if ((cy += 64) == f0 + 576) {
              cy = f0;
              cx += 64;
            }
            if (n > -5 && elect_one()) tma_load_2d(dst + (p < 5 ? 8192 : HALF), &mp.wd, bar, cx, cy);
            if (elect_one()) mbar_expect_tx(bar, n > -5 ? 16384 : 8192);
            if ((cy += 64) == f0 + 576) {
              cy = f0;
              cx += 64;
            }
            if (IMG && n == 8 && L + 1 < NLAYERS) poll_ge(&g_flag[FL_W + j], lds_u32(sb + S_EP) * 18u);
            if (++p == (n > 1 ? 7 : 5)) p = 0;
            if (p == 2) ph ^= 1;
          }
        }
      }
    } else if (warp == 9) {
      auto fetch = [&](const CUtensorMap* map, uint32_t mask) {
        const int lane = tid_now() & 31;
        if ((mask >> lane) & 1)
          tma_load_3d_mc(sb + rank * HALF + lane * TILE, map, sb + B_FX + 72 * rank + 8 * lane, lane * 64, rb * 64 + rank * 32, 0);
        __syncwarp();
      };
      if ((tid_now() & 31) < 18) mbar_expect_tx(sb + B_FX + 8 * (tid_now() & 31), TILE);
      fetch(&mp.x0, (1u << X_EARLY) - 1);
      sts_u32(sb + S_EP, ep1);
      TA0(10);
      {
        const int lane = tid_now() & 31;
        mbar_wait(sb + B_J, 0);
        float2 c = make_float2(0.f, 0.f);
#pragma unroll
        for (int w = 0; w < 8; ++w) {
          const float2 v = lds_f2(sb + OVF + w * 256 + lane * 8);
          c.x += v.x;
          c.y += v.y;
        }
        if (blockIdx.x < 108) *reinterpret_cast<float2*>(g_csq + (blockIdx.x & 3) * NQKV + (blockIdx.x >> 2) * 64 + 2 * lane) = c;
        asm volatile("bar.arrive 6, 96;" ::: "memory");
        if (elect_one()) signal_release(&g_flag[FL_J]);
        TA0(11);
        poll_ge(&g_flag[FL_J], ep1 * 128u);
        TA0(12);
        if (blockIdx.x == 0 && lane < 8) g_claim[lane] = 0u;
        if (lane < 18) {
          const float4 w = ldg_cg_f4(g_wsum + 72 * j + 4 * lane);
          sts_u4(sb + S_WS + lane * 16, __float_as_uint(w.x), __float_as_uint(w.y), __float_as_uint(w.z), __float_as_uint(w.w));
        }
      }
#pragma unroll 1
      for (int n = 0; n < 2 * NLAYERS - 1; ++n) {
        if (n < NLAYERS) {
#pragma unroll 1
          for (int c = tid_now() & 31; c < 54; c += 32) {
            const int part = c / 18, i = c - 18 * part;
            const float* src = g_csq + part * 576 + 72 * j + 4 * (rank ? (i + 2) % 18 : i);
            float4 a = ldg_cg_f4(src), b = ldg_cg_f4(src + NQKV), d = ldg_cg_f4(src + 2 * NQKV);
            a.x += b.x; a.y += b.y; a.z += b.z; a.w += b.w;
            b = ldg_cg_f4(src + 3 * NQKV);
            a.x += b.x + d.x; a.y += b.y + d.y; a.z += b.z + d.z; a.w += b.w + d.w;
            const uint32_t h0 = pack_bf16(a.x, a.y), h1 = pack_bf16(a.z, a.w);
            const uint32_t ad = (i < 16 ? part * 256 + (((i >> 1) ^ (2 * part)) << 4) : 768 + ((part ^ 6) << 4)) + (i & 1) * 8;
            sts_f2(sb + OVF + ad, __uint_as_float(h0), __uint_as_float(h1));
            sts_f2(sb + OVF + (ad ^ 144), __uint_as_float(pack_bf16(a.x - bf_lo(h0), a.y - bf_hi(h0))),
                   __uint_as_float(pack_bf16(a.z - bf_lo(h1), a.w - bf_hi(h1))));
          }
          const int lane = tid_now() & 31;
          if (lane < 10) sts_u4(sb + OVF + 768 + (lane & 1) * 128 + (((3 + (lane >> 1)) ^ 6 ^ (lane & 1)) << 4), 0u, 0u, 0u, 0u);
          fence_proxy_async();
          warp_arrive(sb + B_AUX);
        }
        {
          const int lane = tid_now() & 31;
          const uint32_t bar = sb + B_FX + 8 * min(lane, 17);
#pragma unroll 1
          for (int it = 0; it < SPIN_MAX; ++it)
            if (__all_sync(0xffffffffu, mbar_test(bar, n & 1))) break;
          if (lane < 18) mbar_expect_tx(bar, TILE);
        }
        const unsigned int* fl = &g_flag[n * 512 + rb * 32 + rank * 16 + (tid_now() & 15)];
        if (LAZY) mbar_wait(sb + B_ST + 72 * rank, n & 1);
        uint32_t todo = 0x1FFu;
#pragma unroll 1
        for (int it = 0; todo && it < SPIN_MAX; ++it) {
          unsigned int v;
          asm volatile("ld.relaxed.gpu.global.u32 %0, [%1];" : "=r"(v) : "l"(fl) : "memory");
          const uint32_t ready = __ballot_sync(0xffffffffu, (int)(v - ep1 * 8u) >= 0) & todo;
          if (LAZY > 1 && (n & 1) && !ready && (todo & 0x7F)) __nanosleep(300);
          if (ready) {
            todo &= ~ready;
            fetch(&mp.r, ready);
          }
        }
      }
      uint32_t bid;
      asm volatile("mov.u32 %0, %%ctaid.x;" : "=r"(bid));
      if (elect_one()) g_epoch[bid] = ep1;
    } else {
      const int h = warp & 1;
      if (h) {
        const int lane = tid_now() & 31;
#pragma unroll 1
        for (int i = 0; i < 12; ++i) st_tagged(g_halo + (rb * 8 + j) * 384 + i * 32 + lane, 0u, 0u, 0u, 2 * ep1 - 1);
        if (lane < 16) st_tagged(g_stat + rb * 128 + (lane >> 3) * 64 + 8 * j + (lane & 7), 0u, 0u, 0u, 4 * ep1 - 1);
      }

      auto copy = [&](int hh, int c) {
        if (elect_one()) tma_store_3d(&mp.r, sb + hh * HALF + c * TILE, 64 * c, rb * 64 + hh * 32, 0);
        bulk_commit();
        bulk_wait<0>();
        __syncwarp();
        if (c < 3) asm volatile("fence.acq_rel.gpu;" ::: "memory");
      };
      float s1 = 0.f, s2 = 0.f;
      int kb = 0;
      uint32_t hn = 0;
      auto tile_stats = [&]() {
        const int lane = tid_now() & 31;
        const uint32_t ad = sb + h * HALF + kb * TILE + j * 1024 + (lane & 28) * 32 + (lane & 7) * 16;
        const uint4 u = lds_u4(ad), v = lds_u4(ad ^ 64);
        const uint32_t w[8] = {u.x, u.y, u.z, u.w, v.x, v.y, v.z, v.w};
        float a = 0.f, b = 0.f;
#pragma unroll
        for (int e = 0; e < 8; ++e) {
          const float lo = bf_lo(w[e]), hi = bf_hi(w[e]);
          s1 += lo;
          a += hi;
          s2 = fmaf(lo, lo, s2);
          b = fmaf(hi, hi, b);
        }
        s1 += a;
        s2 += b;
        ++kb;
      };
      unsigned int* fl = &g_flag[rb * 32];
#pragma unroll 1
      for (int n = 0; n < 2 * NLAYERS; ++n, fl += 512) {
        const int L = n >> 1;
        (void)L;
        {
          const int lane = tid_now() & 31;
#pragma unroll 1
          while (kb < 8 + (n & 1)) {
            mbar_wait(sb + B_FX + 72 * h + 8 * kb, n & 1);
            tile_stats();
            if (n == 0 && kb == j + 1) copy(h, j);
          }
          s1 = quad_sum(s1) * ((n & 1) ? 1.0f / DM : 1.0f / 512);
          s2 = fmaf(s1 * s1, (n & 1) ? -576.f : -512.f, quad_sum(s2));
          if (n & 1) {
            s2 = inv_sd(s2 * (1.0f / DM));
            s2 *= s2;
          }
          uint4* gs = g_stat + rb * 128 + h * 64;
          const uint32_t tag = 4 * ep1 + n;
          if ((lane & 3) == 0) st_tagged(gs + 8 * j + (lane >> 2), __float_as_uint(s1) & ~128u, __float_as_uint(s2) & ~128u, 0u, tag);
          s1 = s2 = 0.f;
          kb = 0;
          TA(14 + (n & 1) * 2);
          uint4 u, v;
#pragma unroll 1
          for (int it = 0; it < SPIN_MAX; ++it) {
            u = ld_tagged(gs + 2 * lane);
            v = ld_tagged(gs + 2 * lane + 1);
            if (__all_sync(0xffffffffu, u.w == tag && v.w == tag)) break;
          }
          if (n == 0) named_bar_sync(6, 96);
          if (n & 1) {
            sts_u32(sb + TAB + h * 512 + lane * 16 + 4, u.y);
            sts_u32(sb + TAB + h * 512 + lane * 16 + 12, v.y);
          } else {
            sts_u4(sb + TAB + h * 512 + lane * 16, u.x, u.y, v.x, v.y);
            fence_proxy_async();
          }
          warp_arrive(sb + B_SR);
          TA(15 + (n & 1) * 2);
        }
        if (!((n & 1) | h)) {
          const int lane = tid_now() & 31;
          const uint32_t dst = sb + (2 - rank) * TILE;
          mbar_wait(sb + B_QK, L);
          TA(18);
          if (rb) {
            auto attempt = [&](uint32_t b) {
              if (elect_one()) {
                mbar_expect_tx(sb + B_HP + 8 * b, 6144);
                bulk_load(dst, g_halo + (rb * 8 - 8 + j) * 384, 6144, sb + B_HP + 8 * b);
              }
            };
            attempt(hn & 1);
            __nanosleep(100);
#pragma unroll 1
            for (int it = 0; it < SPIN_MAX; ++it) {
              attempt(~hn & 1);
              mbar_wait(sb + B_HP + 8 * (hn & 1), (hn >> 1) & 1);
              ++hn;
              uint32_t bad = 0;
#pragma unroll
              for (int i = 0; i < 12; ++i) bad |= lds_u32(dst + lane * 16 + 12 + i * 512) ^ (2 * ep1 + L);
              if (__all_sync(0xffffffffu, bad == 0)) break;
            }
          } else {
#pragma unroll 1
            for (int i = 0; i < 12; ++i) sts_u4(dst + lane * 16 + i * 512, 0u, 0u, 0u, 0u);
            __syncwarp();
          }
          if (lane < 2) mbar_arrive(sb + B_NB + 16 * lane);
          TA(19);
          if (rb) {
            mbar_wait(sb + B_HP + 8 * (hn & 1), (hn >> 1) & 1);
            ++hn;
          }
        }
        if (n == 0 && h && (j & 5) == 0) {
          mbar_wait(sb + B_FX + 36 * j + 64, 0);
          copy(j >> 1, 8);
        }
        auto send = [&](int hh, int c) {
          TA(20 + (n & 1) * 20 + c);
          fence_proxy_async();
          if (elect_one()) tma_reduce_3d(&mp.r, sb + hh * HALF + c * TILE, 64 * c, rb * 64 + hh * 32, 0);
          bulk_commit();
        };
        if (!(n & 1)) {
          uint32_t tnext, t;
#pragma unroll 1
          for (int i = 0; i < 5; ++i) {
            const int c = i ? 2 * i - 1 + rank : 0;
            if (i == 1) {
              TA(20 + c);
              named_bar_sync(7 + h, 64);
              if (elect_one()) signal_release(fl + 16 * h + c, 2);
              TA(30 + c);
              continue;
            }
            mbar_wait(sb + B_ST + 72 * h + 8 * i, 0);
            while (true) {
              asm volatile("mov.u32 %0, %%clock;" : "=r"(t));
              if (i == 0 || (int)(t - tnext) >= 0) break;
              __nanosleep(40);
            }
            tnext = i ? tnext + PACE : t + PACE0 + rank * PACE_R;
            if (i == (n ? 4 : 2)) mbar_wait(sb + B_FX + 72 * h, 1);
            if (i == 4) mbar_wait(sb + B_FX + 72 - 72 * h, 1);
            send(h, c);
            bulk_wait<0>();
            if (elect_one()) signal_release(fl + 16 * h + c, i ? 2 : 1);
            TA(30 + c);
          }
        } else {
          if (IMG && n == 1 && NLAYERS > 1 && !h) {
#pragma unroll 1
            for (int s = rb; s < 18; s += 16) {
              const uint32_t bar = sb + B_HP + 8 * (hn & 1), dst = sb + (s >> 4) * HALF + 5 * TILE;
              mbar_wait(sb + B_ST + 72 * (s >> 4), 1);
              load_wq(dst, bar, s);
              mbar_wait(bar, (hn >> 1) & 1);
              ++hn;
              fence_proxy_async();
              __syncwarp();
              if (elect_one()) bulk_store(g_wimg + (j * 18 + s) * 1024, dst, SLOT);
            }
          }
#pragma unroll 1
          for (int a = h ^ 1; a < 9; a += 2) {
            mbar_wait(sb + B_ST + 72 + 8 * a, 1);
            send(1, a);
            mbar_wait(sb + B_ST + 8 * a, 1);
            send(0, a);
            if (n < 2 * NLAYERS - 1) {
              bulk_wait<0>();
              if (elect_one()) {
                signal_release(fl + 16 + a);
                signal_relaxed(fl + a);
                if (IMG && a == 1) {
                  signal_relaxed(&g_flag[FL_W + j], rb < 2 ? 2 : 1);
                  mbar_arrive(sb + B_S1);
                }
              }
              TA(50 + a);
#pragma unroll 1
              while (kb < min(a - 1, ST_END)) {
                mbar_wait(sb + B_FX + 72 * h + 8 * kb, 0);
                tile_stats();
              }
            }
          }
          bulk_wait<0>();
        }
      }
    }
  } else {
    {
      const int t = threadIdx.x, lane = t & 31;
      uint4 sq[5], so[3];
      if (t < 16 * X_PF) asm volatile("prefetch.global.L2 [%0];" ::"l"(x0 + (size_t)(blockIdx.x * 16 + (t & 15)) * DM + (t >> 4) * 64));
#pragma unroll
      for (int i = 0; i < 5; ++i)
        sq[i] = ldg_u4(wqkv + (size_t)((blockIdx.x & 3) + (t >> 3) * 4 + 128 * i) * NQKV + (blockIdx.x >> 2) * 64 + (t & 7) * 8,
                       blockIdx.x < 108 && (i < 4 || t < 128));
#pragma unroll
      for (int i = 0; i < 3; ++i)
        so[i] = ldg_u4(wo + (size_t)((blockIdx.x - 32) * 6 + warp) * DM + (i * 32 + lane) * 8,
                       blockIdx.x >= 32 && warp < 6 && (i < 2 || lane < 8));
      asm volatile("setmaxnreg.inc.sync.aligned.u32 240;");
      float c[8];
#pragma unroll
      for (int e = 0; e < 8; ++e) c[e] = 0.f;
#pragma unroll
      for (int i = 0; i < 5; ++i) {
        c[0] += bf_lo(sq[i].x); c[1] += bf_hi(sq[i].x); c[2] += bf_lo(sq[i].y); c[3] += bf_hi(sq[i].y);
        c[4] += bf_lo(sq[i].z); c[5] += bf_hi(sq[i].z); c[6] += bf_lo(sq[i].w); c[7] += bf_hi(sq[i].w);
      }
#pragma unroll
      for (int n = 4; n >= 2; n >>= 1) {
        const bool up = lane & (4 * n);
#pragma unroll
        for (int e = 0; e < n; ++e) c[e] = (up ? c[e + n] : c[e]) + __shfl_xor_sync(0xffffffffu, up ? c[e] : c[e + n], 4 * n);
      }
      sts_f2(sb + OVF + warp * 256 + (lane & 7) * 32 + (lane & 24), c[0], c[1]);
      float r = sum8(so[0]) + sum8(so[1]) + sum8(so[2]);
#pragma unroll
      for (int o = 1; o < 32; o <<= 1) r += __shfl_xor_sync(0xffffffffu, r, o);
      if (lane == 0 && blockIdx.x >= 32 && warp < 6) g_wsum[(blockIdx.x - 32) * 6 + warp] = r;
      cluster_wait();
      warp_arrive(sb + B_J);
      TA0(13);
    }
#pragma unroll 1
    for (uint32_t L = 0; L < NLAYERS; ++L) {
      {
        const int wg = warp >> 2;
        float acc[108];
        const uint32_t da0 = desc_lo_a(sb + wg * HALF), db0 = desc_lo_b(sb + RING, 4096);
        int p = 2;
        uint32_t ph = L;
        auto step = [&](int kb, auto U, auto FIRST) {
          constexpr int u = decltype(U)::value, first = decltype(FIRST)::value == 1;
          constexpr bool last = decltype(FIRST)::value == 2;
          wgmma_fence();
#pragma unroll
          for (int k = 0; k < 2; ++k)
            wgmma_ss<216>(acc, desc_from_lo(da0 + kb * 512 + u * 4 + k * 2), desc_from_lo(db0 + p * 1024 + k * 128), !first || u || k);
          wgmma_commit();
          if (last && wg) asm volatile("bar.arrive 5, 256;" ::: "memory");
          const int prev = p == 0 ? 4 : p - 1;
          if (++p == 5) p = 0;
          if (p == 2) ph ^= 1;
          if (!last) {
            if (u) mbar_wait2(sb + B_FX + 72 * wg + 8 * kb + 8, 0, sb + B_FULL + 8 * p, ph);
            else mbar_wait(sb + B_FULL + 8 * p, ph);
          }
          if (!first || u) {
            wgmma_wait<1>();
            release_slot(sb, prev);
          }
        };
        mbar_wait2(sb + B_FX + 72 * wg, 0, sb + B_FULL + 8 * p, ph);
        TR(1);
        step(0, IC<0>{}, IC<1>{});
        step(0, IC<1>{}, IC<1>{});
        float s1[2] = {0.f, 0.f}, s2[2] = {0.f, 0.f};
        bool todo = true;
        const int stop = wg ? 8 : Q_H;
        auto last_tile = [&]() {
          const int lane = tid_now() & 31;
#pragma unroll
          for (int r = 0; r < 2; ++r) {
            const uint32_t ad = sb + wg * HALF + 8 * TILE + (warp & 3) * 2048 + r * 1024 + (lane & 28) * 32 + (lane & 7) * 16;
            const uint4 u = lds_u4(ad), v = lds_u4(ad ^ 64);
            const uint32_t w[8] = {u.x, u.y, u.z, u.w, v.x, v.y, v.z, v.w};
            float a = 0.f, b = 0.f, c = 0.f, d = 0.f;
#pragma unroll
            for (int e = 0; e < 8; ++e) {
              const float lo = bf_lo(w[e]), hi = bf_hi(w[e]);
              a += lo;
              b += hi;
              c = fmaf(lo, lo, c);
              d = fmaf(hi, hi, d);
            }
            s1[r] = quad_sum(a + b) * (1.0f / 64);
            s2[r] = fmaf(s1[r] * s1[r], -64.f, quad_sum(c + d));
          }
          todo = false;
        };
#pragma unroll 1
        for (int kb = 1; kb < 9; ++kb) {
          TR(1 + kb);
          if (Q_H < 8 && kb == stop) mbar_wait(sb + B_FX + 72 * wg + 64, 0);
          if (todo && kb >= (wg ? Q_ST1 : Q_ST0) && __all_sync(0xffffffffu, mbar_test(sb + B_FX + 72 * wg + 64, 0))) last_tile();
          if (kb == stop) break;
          step(kb, IC<0>{}, IC<0>{});
          step(kb, IC<1>{}, IC<0>{});
        }
        const int tid = tid_now(), lane = tid & 31, g = lane >> 2, q = lane & 3;
        if (lane == 0 && wg == 0) mbar_arrive(sb + B_QK);
        mbar_wait2(sb + B_SR, 0, sb + B_AUX, L);
        float2 st0 = lds_f2(sb + TAB + (warp * 16 + g) * 8), st1 = lds_f2(sb + TAB + (warp * 16 + g) * 8 + 64);
        s1[0] -= st0.x;
        s1[1] -= st1.x;
        st0.x = fmaf(s1[0], 1.0f / 9, st0.x);
        st1.x = fmaf(s1[1], 1.0f / 9, st1.x);
        st0.y = fmaf(s1[0] * s1[0], 512.f / 9, st0.y + s2[0]);
        st1.y = fmaf(s1[1] * s1[1], 512.f / 9, st1.y + s2[1]);
        if (wg == 0) named_bar_sync(5, 256);
        wgmma_fence();
        wgmma_rs<216>(acc, q ? 0u : pack_bf16(-st0.x, -st0.x), q ? 0u : pack_bf16(-st1.x, -st1.x), 0u, 0u, desc_sbo(desc_lo_b(sb + OVF, 256), 0), 1);
        wgmma_commit();
        if (Q_H < 8) {
#pragma unroll 1
          for (int kb = stop; kb < 8; ++kb) {
            step(kb, IC<0>{}, IC<0>{});
            step(kb, IC<1>{}, IC<0>{});
          }
        }
        step(8, IC<0>{}, IC<0>{});
        step(8, IC<1>{}, IC<2>{});
        TR(10);
        st0.y = inv_sd(st0.y * (1.0f / DM));
        st1.y = inv_sd(st1.y * (1.0f / DM));
        const uint32_t ep1 = lds_u32(sb + S_EP), role = lds_u32(sb + S_ROLE);
        const bool first = (warp & 5) == 0 && role < 4;
        const bool e0 = 2 * q > g, e1 = 2 * q + 1 > g;
        float fs[2][2], fp[2][2], fb[2];
        {
          const float k0 = __shfl_sync(0xffffffffu, st0.y, 8 * q), k1 = __shfl_sync(0xffffffffu, st0.y, 8 * q + 4);
          const float c = 0.23570226039551584f * 1.4426950408889634f;
          fp[0][0] = e0 ? 1.f : k0;
          fp[0][1] = e1 ? 1.f : k1;
          fp[1][0] = e0 ? k0 : 1.f;
          fp[1][1] = e1 ? k1 : 1.f;
#pragma unroll
          for (int i = 0; i < 4; ++i) fs[i >> 1][i & 1] = fp[i >> 1][i & 1] * ((i >> 1) ? st1.y : st0.y) * c;
          fb[0] = first && e0 ? -INFINITY : 0.f;
          fb[1] = first && e1 ? -INFINITY : 0.f;
        }
        const int sw = (warp & 1) ? warp + 3 : warp + 1;
        const uint64_t nbp = sw >= 8 ? (uint64_t)(g_halo + (role * 2 + rank) * 384 + (warp & 2) * 96 + lane)
                                     : (uint64_t)(smem + (sw >> 2) * HALF + (2 + 2 * (sw & 1) - rank) * TILE + (sw & 2) * 1536 + lane * 16);
        const uint32_t nbb = lane ? mapa(sb + B_RX + 8 * wg, rank ^ 1) : mapa(sb + B_NB + 8 * (sw & 7), rank);
        const bool nba = lane ? lane == 1 : sw < 8;
        if (tid == 128 * wg) mbar_expect_tx(sb + B_OX + 8 * wg, 10240);
        __syncwarp();
        wgmma_wait<0>();
        release_slot(sb, 4);
        TS(1);
        uint32_t Q[2][9], K[3][9], V[3][9];
        auto pack = [&](auto R) {
          constexpr int r = decltype(R)::value;
#pragma unroll
          for (int i = 0; i < 9; ++i) {
            const int c = (i + 9 - r) % 9, jv = c < 8 ? 64 + 4 * c : 104;
            V[2][i] = movm(pack_bf16(acc[jv + 2] * st1.y, acc[jv + 3] * st1.y));
          }
#pragma unroll
          for (int i = 0; i < 9; ++i) {
            const int c = (i + 9 - r) % 9, jk = c < 8 ? 32 + 4 * c : 100;
            K[2][i] = pack_bf16(acc[jk + 2] * st1.y, acc[jk + 3] * st1.y);
          }
#pragma unroll
          for (int i = 0; i < 6; ++i) {
            const uint32_t(&d)[9] = i < 3 ? K[2] : V[2];
            st_tagged_any(nbp + i * 512, d[3 * (i % 3)], d[3 * (i % 3) + 1], d[3 * (i % 3) + 2], 2 * ep1 + L);
          }
          __syncwarp();
          mbar_arrive_if(nbb, nba);
#pragma unroll
          for (int i = 0; i < 9; ++i) {
            const int c = (i + 9 - r) % 9, jq = c < 8 ? 4 * c : 96, jk = c < 8 ? 32 + 4 * c : 100, jv = c < 8 ? 64 + 4 * c : 104;
            V[1][i] = movm(pack_bf16(acc[jv], acc[jv + 1]));
            Q[0][i] = pack_bf16(acc[jq], acc[jq + 1]);
            Q[1][i] = pack_bf16(acc[jq + 2], acc[jq + 3]);
            K[1][i] = pack_bf16(acc[jk], acc[jk + 1]);
          }
        };
        if (rank) pack(IC<1>{});
        else pack(IC<0>{});
        uint32_t qf[4][2], ql[4][2];
        float sc[4][3][4];
        auto logits = [&](int t) {
#pragma unroll
          for (int h = 0; h < 4; ++h) {
            mma_1688(sc[h][t], ql[h][0], ql[h][1], K[t][2 * h + 2]);
            mma_16816(sc[h][t], qf[h][0], qf[h][1], Q[0][2 * h + 1], Q[1][2 * h + 1], K[t][2 * h], K[t][2 * h + 1]);
          }
        };
#pragma unroll
        for (int i = 0; i < 8; ++i) {
          qf[i >> 1][i & 1] = q >= (i >> 1) ? Q[i & 1][i & 6] : 0u;
          ql[i >> 1][i & 1] = q <= (i >> 1) ? Q[i & 1][(i & 6) + 2] : 0u;
        }
        logits(1);
        logits(2);
        float2 ws[9];
#pragma unroll
        for (int i = 0; i < 9; ++i) ws[i] = lds_f2(sb + S_WS + i * 32 + 8 * q);
        uint32_t of[9][2];
        float o0[9][2];
        auto rows = [&](auto R, float(&o)[9][2]) {
          constexpr int r = decltype(R)::value;
          float pr[4][2], mx[4];
#pragma unroll
          for (int h = 0; h < 4; ++h) {
            pr[h][0] = fmaf(e0 ? sc[h][r][2 * r] : sc[h][r + 1][2 * r], fs[r][0], r ? 0.f : fb[0]);
            pr[h][1] = fmaf(e1 ? sc[h][r][2 * r + 1] : sc[h][r + 1][2 * r + 1], fs[r][1], r ? 0.f : fb[1]);
            mx[h] = fmaxf(pr[h][0], pr[h][1]);
          }
#pragma unroll
          for (int i = 0; i < 8; ++i) mx[i & 3] = fmaxf(mx[i & 3], __shfl_xor_sync(0xffffffffu, mx[i & 3], 1 + (i >> 2)));
#pragma unroll
          for (int h = 0; h < 4; ++h) {
#pragma unroll
            for (int e = 0; e < 2; ++e) asm("ex2.approx.ftz.f32 %0, %1;" : "=f"(pr[h][e]) : "f"(pr[h][e] - mx[h]));
            mx[h] = pr[h][0] + pr[h][1];
            pr[h][0] *= fp[r][0];
            pr[h][1] *= fp[r][1];
          }
#pragma unroll
          for (int i = 0; i < 8; ++i) mx[i & 3] += __shfl_xor_sync(0xffffffffu, mx[i & 3], 1 + (i >> 2));
          const uint32_t me = (e0 ? 0xFFFFu : 0u) | (e1 ? 0xFFFF0000u : 0u);
          uint32_t pp[4];
#pragma unroll
          for (int h = 0; h < 4; ++h) {
            pp[h] = pack_bf16(pr[h][0], pr[h][1]);
            asm("rcp.approx.ftz.f32 %0, %1;" : "=f"(mx[h]) : "f"(mx[h]));
          }
#pragma unroll
          for (int i = 0; i < 9; ++i) {
            const int h = i < 4 ? 0 : i < 5 ? 1 : 2;
            float d[4];
            mma_16816_z(d, pp[h] & me, pp[h + 1] & me, pp[h] & ~me, pp[h + 1] & ~me, V[r][i], V[r + 1][i]);
            const bool up = i == 2 * h + 2 ? q > h : i > 2 * h + 2;
            const float inv = up ? mx[h + 1] : mx[h];
            o[i][0] = (up ? d[2] : d[0]) * inv;
            o[i][1] = (up ? d[3] : d[1]) * inv;
            of[i][r] = pack_bf16(o[i][0], o[i][1]);
          }
        };
        auto shift = [&](const float(&o)[9][2]) {
          float a = 0.f, b = 0.f, c = 0.f;
#pragma unroll
          for (int i = 0; i < 3; ++i) {
            a = fmaf(o[i][0], ws[i].x, fmaf(o[i][1], ws[i].y, a));
            b = fmaf(o[i + 3][0], ws[i + 3].x, fmaf(o[i + 3][1], ws[i + 3].y, b));
            c = fmaf(o[i + 6][0], ws[i + 6].x, fmaf(o[i + 6][1], ws[i + 6].y, c));
          }
          return a + b + c;
        };
        rows(IC<1>{}, o0);
        float sh1 = shift(o0);
        mbar_wait3(sb + B_FULL, L ^ 1, sb + B_RX + 8 * wg, L, sb + B_NB + 8 * warp, L);
#pragma unroll
        for (int i = 0; i < 6; ++i) {
          const uint4 u = lds_u4(sb + wg * HALF + (2 + 2 * (warp & 1) - rank) * TILE + (warp & 2) * 1536 + lane * 16 + i * 512);
          uint32_t(&d)[9] = i < 3 ? K[0] : V[0];
          d[3 * (i % 3)] = u.x;
          d[3 * (i % 3) + 1] = u.y;
          d[3 * (i % 3) + 2] = u.z;
        }
        TS(3);
        logits(0);
        rows(IC<0>{}, o0);
        TS(5);
        float wa[3][32];
        const uint32_t dw0 = desc_lo_b(sb + RING, 0);
        wgmma_fence();
#pragma unroll
        for (int k = 0; k < 5; ++k)
          wgmma_rs<64>(wa[0], of[2 * k][0], of[2 * k][1], k < 4 ? of[2 * k + 1][0] : 0u, k < 4 ? of[2 * k + 1][1] : 0u,
                       desc_sbo(dw0 + k * 128, k < 4 ? 1024 : 0), k);
        wgmma_commit();
        const uint32_t xa = sb + wg * HALF + 3 * TILE + (warp & 3) * 2048 + lane * 16;
        const uint32_t xr = mapa(xa + (rank ^ 1) * TILE, rank ^ 1), xb = mapa(sb + B_OX + 8 * wg, rank ^ 1);
#pragma unroll
        for (int i = 0; i < 4; ++i) st_async_u4(xr + i * 512, xb, of[2 * i][0], of[2 * i][1], of[2 * i + 1][0], of[2 * i + 1][1]);
        float sh0 = fmaf(quad_sum(shift(o0)), 1.0f / DM, st0.x * 0.125f);
        sh1 = fmaf(quad_sum(sh1), 1.0f / DM, st1.x * 0.125f);
        st_async_u4(xr + 2 * TILE, xb, of[8][0], of[8][1], __float_as_uint(sh0), __float_as_uint(sh1));
        wgmma_wait<0>();
        stage_tile(wa[0], 1.f, -sh0, 1.f, -sh1, sb, 0, 0, 1);
        TS(6);
        uint4 xv[5];
        auto issue = [&](auto I, auto PART) {
          constexpr int i = decltype(I)::value, part = decltype(PART)::value;
          const uint32_t lo = dw0 + (2 * i - 1) * (WOA / 16);
          if (part & 1) mbar_wait(sb + B_FULL + 8 * i, (i == 1) ^ L);
          wgmma_fence();
          if (part & 1) {
#pragma unroll
            for (int k = 0; k < 4; ++k)
              wgmma_rs<64>(wa[i % 3], of[2 * k][0], of[2 * k][1], of[2 * k + 1][0], of[2 * k + 1][1], desc_sbo(lo + k * 128, 1024), k);
          }
          if (part & 2) {
            wgmma_rs<64>(wa[i % 3], of[8][0], of[8][1], xv[4].x, xv[4].y, desc_sbo(lo + 512, WOA), 1);
#pragma unroll
            for (int k = 0; k < 4; ++k)
              wgmma_rs<64>(wa[i % 3], xv[k].x, xv[k].y, xv[k].z, xv[k].w, desc_sbo(lo + WOA / 16 + k * 128, 1024), 1);
          }
          wgmma_commit();
        };
        issue(IC<1>{}, IC<1>{});
        if (q < 2) sts_u32(sb + TAB + (warp * 16 + g + 8 * q) * 8, __float_as_uint(q ? sh1 : sh0));
        mbar_wait(sb + B_OX + 8 * wg, L);
#pragma unroll
        for (int i = 0; i < 5; ++i) xv[i] = lds_u4(xa + rank * TILE + (i < 4 ? i * 512 : 2 * TILE));
        sh0 += __uint_as_float(xv[4].z);
        sh1 += __uint_as_float(xv[4].w);
        TS(4);
        issue(IC<1>{}, IC<2>{});
        wgmma_wait<0>();
        release_slot(sb, 0);
        stage_tile(wa[1], 1.f, -sh0, 1.f, -sh1, sb, 1 + rank, 1, 1);
        mbar_wait(sb + B_ST, 0);
        issue(IC<2>{}, IC<3>{});
        issue(IC<3>{}, IC<3>{});
        wgmma_wait<1>();
        release_slot(sb, 1);
        issue(IC<4>{}, IC<3>{});
        stage_tile(wa[2], 1.f, -sh0, 1.f, -sh1, sb, 3 + rank, 0, 0);
        wgmma_wait<1>();
        release_slot(sb, 2);
        stage_tile(wa[0], 1.f, -sh0, 1.f, -sh1, sb, 5 + rank, 0, 0);
        wgmma_wait<0>();
        release_slot(sb, 3);
        release_slot(sb, 4);
        stage_tile(wa[1], 1.f, -sh0, 1.f, -sh1, sb, 7 + rank, 2, 7);
        TS(7);
      }
      uint32_t hreg[9][16];
      {
        const int wg = warp >> 2;
        float acc[64];
        int p = 0;
        uint32_t ph = L;
        const uint32_t da0 = desc_lo_a(sb + wg * HALF), db0 = desc_lo_b(sb + RING, 8192);
        float prod[32];
        {
          float acc0[64], acc1[64], acc2[64];
#pragma unroll
          for (int i = 0; i < 64; ++i) acc0[i] = acc1[i] = acc2[i] = 0.f;
          auto step = [&](float(&d)[64], int kb, bool rel) {
            mbar_wait(sb + B_FULL + 8 * p, ph);
            wgmma_fence();
#pragma unroll
            for (int k = 0; k < 4; ++k)
              wgmma_ss<128>(d, desc_from_lo(da0 + kb * 512 + k * 2), desc_from_lo(db0 + p * 1024 + k * 128), 1);
            wgmma_commit();
            wgmma_wait<1>();
            release_slot(sb, p == 0 ? 4 : p - 1, rel);
            if (++p == 5) p = 0;
            if (p == 2) ph ^= 1;
          };
#pragma unroll 1
          for (int kb = 0; kb < 9; ++kb) {
            mbar_wait(sb + B_FX + 72 * wg + 8 * kb, 1);
            if (kb == 0) TS(9);
            TR(16 + kb);
            step(acc0, kb, kb > 0);
            step(acc1, kb, true);
            step(acc2, kb, true);
          }
#pragma unroll
          for (int i = 0; i < 16; ++i) {
            hreg[0][i] = pack_bf16(acc0[2 * i] * acc0[32 + 2 * i], acc0[2 * i + 1] * acc0[33 + 2 * i]);
            hreg[1][i] = pack_bf16(acc1[2 * i] * acc1[32 + 2 * i], acc1[2 * i + 1] * acc1[33 + 2 * i]);
          }
          mbar_wait(sb + B_FULL + 8 * p, ph);
          wgmma_wait<0>();
#pragma unroll
          for (int i = 0; i < 32; ++i) prod[i] = acc2[i] * acc2[32 + i];
        }
#pragma unroll
        for (int t = 2; t < 8; ++t)
#pragma unroll
          for (int i = 0; i < 16; ++i) hreg[t][i] = 0u;
        TS(10);
#pragma unroll 1
        for (int t = 3; t < 9; ++t) {
          wgmma_fence();
#pragma unroll
          for (int k = 0; k < 4; ++k)
            wgmma_ss<128>(acc, desc_from_lo(da0 + k * 2), desc_from_lo(db0 + p * 1024 + k * 128), k != 0);
          wgmma_commit();
          release_slot(sb, p == 0 ? 4 : p - 1);
#pragma unroll
          for (int i = 0; i < 32; ++i) asm volatile("" : "+f"(prod[i]));
#pragma unroll
          for (int i = 0; i < 16; ++i) hreg[8][i] = pack_bf16(prod[2 * i], prod[2 * i + 1]);
          if (++p == 5) p = 0;
          if (p == 2) ph ^= 1;
          mbar_wait(sb + B_FULL + 8 * p, ph);
#pragma unroll 1
          for (int kb = 1; kb < 9; ++kb) {
            wgmma_fence();
#pragma unroll
            for (int k = 0; k < 4; ++k)
              wgmma_ss<128>(acc, desc_from_lo(da0 + kb * 512 + k * 2), desc_from_lo(db0 + p * 1024 + k * 128), 1);
            wgmma_commit();
            if (kb == 1) {
#pragma unroll
              for (int tt = 2; tt < 8; ++tt)
                if (t == tt + 1) {
#pragma unroll
                  for (int i = 0; i < 16; ++i) asm volatile("mov.b32 %0, %1;" : "=r"(hreg[tt][i]) : "r"(hreg[8][i]));
                }
            }
            const int done = p == 0 ? 4 : p - 1;
            if (++p == 5) p = 0;
            if (p == 2) ph ^= 1;
            if (GU_PRE) mbar_wait(sb + B_FULL + 8 * p, ph);
            wgmma_wait<1>();
            release_slot(sb, done);
            if (!GU_PRE) mbar_wait(sb + B_FULL + 8 * p, ph);
          }
          wgmma_wait<0>();
#pragma unroll
          for (int i = 0; i < 32; ++i) prod[i] = acc[i] * acc[32 + i];
          TR(32 + t);
        }
#pragma unroll
        for (int i = 0; i < 16; ++i) hreg[8][i] = pack_bf16(prod[2 * i], prod[2 * i + 1]);
      }
      TS(11);
      {
        float accA[32], accB[32];
#pragma unroll
        for (int i = 16; i < 32; ++i) accB[i] = 0.f;
        int p = 1;
        uint32_t ph = L;
        const uint32_t db0 = desc_lo_b(sb + RING, 8192);
        int prev = 0, left = 35;
        auto stage = [&](auto S, auto NU, bool rel) {
          constexpr int s = decltype(S)::value;
          const uint32_t dlo = p < 5 ? db0 + p * 1024 : db0 - RING / 16 + 1024 + p * 512, dv = p < 5 ? 512 : HALF / 16;
          wgmma_fence();
#pragma unroll
          for (int v = 0; v < decltype(NU)::value; ++v) {
            const int u = 2 * s + v, kq = u % 9;
#pragma unroll
            for (int k = 0; k < 4; ++k)
              wgmma_rs<64>(u >= 9 ? accB : accA, hreg[kq][4 * k], hreg[kq][4 * k + 1], hreg[kq][4 * k + 2], hreg[kq][4 * k + 3],
                           desc_from_lo(dlo + v * dv + k * 128), (kq | k) != 0);
          }
          wgmma_commit();
          const int done = prev;
          prev = p;
          --left;
          if (++p == (left > 0 ? 7 : 5)) p = 0;
          if (p == 2) ph ^= 1;
          if (decltype(NU)::value == 2) mbar_wait(sb + B_FULL + 8 * p, ph ^ (p >= 5));
          if (rel) {
            wgmma_wait<1>();
            release_slot(sb, done, done < 5 || left > 1);
          }
        };
        stage(IC<0>{}, IC<2>{}, false);
        release_slot(sb, 0);
        mbar_wait(sb + B_SR, 1);
        release_slot(sb, 5);
        release_slot(sb, 6);
        const uint32_t ta = sb + TAB + warp * 128 + (tid_now() & 28) * 2;
        const float2 t0 = lds_f2(ta), t1 = lds_f2(ta + 64);
        const float m0 = t0.y, c0 = t0.x, m1 = t1.y, c1 = t1.x;
#pragma unroll 1
        for (int i = 0; i < 4; ++i) {
          stage(IC<1>{}, IC<2>{}, true);
          if (i) stage_tile<2, 4>(accB, m0, c0, m1, c1, sb, 2 * i - 1, 0, 0);
          stage(IC<2>{}, IC<2>{}, true);
          if (i) stage_done(sb, 2 * i - 1, 1);
          stage(IC<3>{}, IC<2>{}, true);
          stage(IC<4>{}, IC<2>{}, true);
          stage(IC<5>{}, IC<2>{}, true);
          stage_tile<0, 2>(accA, m0, c0, m1, c1, sb, 2 * i, 0, 0);
          TR(48 + 2 * i);
          stage(IC<6>{}, IC<2>{}, true);
          stage_tile<2, 4>(accA, m0, c0, m1, c1, sb, 2 * i, 0, 0);
          stage(IC<7>{}, IC<2>{}, true);
          stage_done(sb, 2 * i, 1);
          if (i == 3 && (tid_now() & 31) == 0) mbar_arrive(sb + B_XF);
          stage(IC<8>{}, IC<2>{}, true);
          stage(IC<0>{}, IC<2>{}, true);
          if (IMG && i == 2 && L + 1 < NLAYERS) mbar_wait(sb + B_S1, 0);
          if (i == 3) mbar_wait(sb + B_XF, L);
          stage_tile<0, 2>(accB, m0, c0, m1, c1, sb, 2 * i + 1, 0, 0);
          TR(49 + 2 * i);
        }
        stage(IC<1>{}, IC<2>{}, true);
        stage_tile<2, 4>(accB, m0, c0, m1, c1, sb, 7, 7, DN_LATE ? 0 : 1);
        stage(IC<2>{}, IC<2>{}, true);
        if (DN_LATE) stage_done(sb, 7, 1);
        stage(IC<3>{}, IC<2>{}, true);
        stage(IC<4>{}, IC<1>{}, true);
        wgmma_wait<0>();
        release_slot(sb, 1);
        stage_tile(accA, m0, c0, m1, c1, sb, 8, 8, 1);
        TR(56);
        TS(12);
      }
    }
  }
}

__global__ void probe_kernel() {}

typedef CUresult (*PFN_tmEncode)(CUtensorMap*, CUtensorMapDataType, cuuint32_t, void*, const cuuint64_t*,
                                 const cuuint64_t*, const cuuint32_t*, const cuuint32_t*, CUtensorMapInterleave,
                                 CUtensorMapSwizzle, CUtensorMapL2promotion, CUtensorMapFloatOOBfill);

static void encode_2d(PFN_tmEncode fn, CUtensorMap* m, const void* ptr, uint64_t inner, uint64_t outer, uint32_t box_inner,
                      uint32_t box_outer) {
  cuuint64_t dims[2] = {inner, outer};
  cuuint64_t strides[1] = {inner * 2};
  cuuint32_t box[2] = {box_inner, box_outer};
  cuuint32_t estr[2] = {1, 1};
  fn(m, CU_TENSOR_MAP_DATA_TYPE_BFLOAT16, 2, const_cast<void*>(ptr), dims, strides, box, estr,
     CU_TENSOR_MAP_INTERLEAVE_NONE, CU_TENSOR_MAP_SWIZZLE_128B, CU_TENSOR_MAP_L2_PROMOTION_L2_256B,
     CU_TENSOR_MAP_FLOAT_OOB_FILL_NONE);
}

static void encode_3d(PFN_tmEncode fn, CUtensorMap* m, const void* ptr, uint64_t d0, uint64_t d1, uint64_t d2, uint64_t s1,
                      uint64_t s2, uint32_t b0, uint32_t b1, uint32_t b2, CUtensorMapL2promotion prom) {
  cuuint64_t dims[3] = {d0, d1, d2};
  cuuint64_t strides[2] = {s1, s2};
  cuuint32_t box[3] = {b0, b1, b2};
  cuuint32_t estr[3] = {1, 1, 1};
  fn(m, CU_TENSOR_MAP_DATA_TYPE_BFLOAT16, 3, const_cast<void*>(ptr), dims, strides, box, estr, CU_TENSOR_MAP_INTERLEAVE_NONE,
     CU_TENSOR_MAP_SWIZZLE_128B, prom, CU_TENSOR_MAP_FLOAT_OOB_FILL_NONE);
}

}

extern "C" void kernel_launch(void* const* d_in, const int* in_sizes, int n_in, void* d_out, int out_size) {
  const __nv_bfloat16* x0 = (const __nv_bfloat16*)d_in[0];
  const __nv_bfloat16* wqkv = (const __nv_bfloat16*)d_in[1];
  const __nv_bfloat16* wo = (const __nv_bfloat16*)d_in[2];
  const __nv_bfloat16* wg = (const __nv_bfloat16*)d_in[4];
  const __nv_bfloat16* wu = (const __nv_bfloat16*)d_in[5];
  const __nv_bfloat16* wd = (const __nv_bfloat16*)d_in[6];
  static PFN_tmEncode enc = nullptr;
  if (!enc) {
    void* fn = nullptr;
    cudaDriverEntryPointQueryResult qr;
    cudaGetDriverEntryPoint("cuTensorMapEncodeTiled", &fn, cudaEnableDefault, &qr);
    enc = (PFN_tmEncode)fn;
  }
  Maps mp;
  encode_3d(enc, &mp.x0, x0, DM, SEQ / 2, 2, DM * 4, DM * 2, 64, 32, 2, CU_TENSOR_MAP_L2_PROMOTION_L2_256B);
  encode_3d(enc, &mp.r, d_out, DM, SEQ / 2, 2, DM * 4, DM * 2, 64, 32, 2, CU_TENSOR_MAP_L2_PROMOTION_L2_256B);
  encode_3d(enc, &mp.wq, wqkv, 576, 576, 3, NQKV * 2, 576 * 2, 64, 32, 3, CU_TENSOR_MAP_L2_PROMOTION_L2_128B);
  encode_2d(enc, &mp.wo, wo, DM, DM, 64, 72);
  encode_2d(enc, &mp.wg, wg, FF, DM, 64, 64);
  encode_2d(enc, &mp.wu, wu, FF, DM, 64, 64);
  encode_2d(enc, &mp.wd, wd, DM, FF, 64, 64);
  cudaFuncSetAttribute(mega_kernel, cudaFuncAttributeMaxDynamicSharedMemorySize, SMEM_BYTES);
  static int small_gpc = -1;
  if (small_gpc < 0) {
    cudaFuncSetAttribute(probe_kernel, cudaFuncAttributeMaxDynamicSharedMemorySize, SMEM_BYTES);
    cudaFuncSetAttribute(probe_kernel, cudaFuncAttributeNonPortableClusterSizeAllowed, 1);
    int n[2] = {0, 0};
    for (int i = 0; i < 2; ++i) {
      cudaLaunchConfig_t cfg = {};
      cfg.gridDim = dim3(128);
      cfg.blockDim = dim3(384);
      cfg.dynamicSmemBytes = SMEM_BYTES;
      cudaLaunchAttribute at;
      at.id = cudaLaunchAttributeClusterDimension;
      at.val.clusterDim.x = 8 << i;
      at.val.clusterDim.y = at.val.clusterDim.z = 1;
      cfg.attrs = &at;
      cfg.numAttrs = 1;
      if (cudaOccupancyMaxActiveClusters(&n[i], probe_kernel, &cfg) != cudaSuccess) cudaGetLastError();
    }
    small_gpc = n[0] == 15 && n[1] == 7;
  }
  mega_kernel<<<128, 384, SMEM_BYTES, cudaStreamPerThread>>>(mp, x0, wqkv, wo, (__nv_bfloat16*)d_out, small_gpc);
}
```

```cpp
#include <cuda_runtime.h>
#include <cuda_bf16.h>
#include <cuda.h>
#include <stdint.h>

namespace {

constexpr int SEQ = 2048, DM = 576, FF = 4608, NQKV = 1728, NCTA = 132;

constexpr int FL_J = 64 * 32, FL_W = FL_J + 32;
struct Scratch {
  unsigned int flag[FL_W + 32];
  unsigned int epoch[160];
  unsigned int claim[32];
  float wsum[DM];
  float csq[4 * NQKV];
  uint4 stat[SEQ];
  uint4 halo[128 * 384];
  uint4 hx[128 * 384];
  uint4 himg[36 * 1024];
  uint4 wimg[8 * 18 * 1024];
};
__device__ __align__(1024) Scratch gs_;

__device__ __forceinline__ uint32_t smem_u32(const void* p) { return (uint32_t)__cvta_generic_to_shared(p); }
__device__ __forceinline__ void mbar_init(uint32_t bar, uint32_t count) {
  asm volatile("mbarrier.init.shared::cta.b64 [%0], %1;" ::"r"(bar), "r"(count) : "memory");
}
__device__ __forceinline__ void mbar_expect_tx(uint32_t bar, uint32_t bytes) {
  asm volatile("mbarrier.arrive.expect_tx.shared::cta.b64 _, [%0], %1;" ::"r"(bar), "r"(bytes) : "memory");
}
__device__ __forceinline__ void mbar_arrive(uint32_t bar) {
  asm volatile("mbarrier.arrive.shared::cta.b64 _, [%0];" ::"r"(bar) : "memory");
}
#define SPIN_LIMIT "1048576"
#define SPIN_MAX 1048576
__device__ __forceinline__ void mbar_wait(uint32_t bar, uint32_t parity) {
  asm volatile(
      "{\n.reg .pred p, c;\n.reg .u32 n;\nmov.u32 n, 0;\n"
      "WAIT:\nmbarrier.try_wait.parity.shared::cta.b64 p, [%0], %1;\n"
      "add.u32 n, n, 1;\nsetp.lt.and.u32 c, n, " SPIN_LIMIT ", !p;\n@c bra.uni WAIT;\n}"
      :
      : "r"(bar), "r"(parity)
      : "memory");
}
__device__ __forceinline__ void mbar_wait2(uint32_t a, uint32_t pa, uint32_t b, uint32_t pb) {
  asm volatile(
      "{\n.reg .pred p, q, c;\n.reg .u32 n;\nmov.u32 n, 0;\n"
      "WAIT:\nmbarrier.try_wait.parity.shared::cta.b64 p, [%0], %1;\nmbarrier.try_wait.parity.shared::cta.b64 q, [%2], %3;\n"
      "add.u32 n, n, 1;\nand.pred p, p, q;\nsetp.lt.and.u32 c, n, " SPIN_LIMIT ", !p;\n@c bra.uni WAIT;\n}"
      :
      : "r"(a), "r"(pa), "r"(b), "r"(pb)
      : "memory");
}
__device__ __forceinline__ void mbar_wait3(uint32_t a, uint32_t pa, uint32_t b, uint32_t pb, uint32_t d, uint32_t pd) {
  asm volatile(
      "{\n.reg .pred p, q, r, c;\n.reg .u32 n;\nmov.u32 n, 0;\n"
      "WAIT:\nmbarrier.try_wait.parity.shared::cta.b64 p, [%0], %1;\nmbarrier.try_wait.parity.shared::cta.b64 q, [%2], %3;\n"
      "mbarrier.try_wait.parity.shared::cta.b64 r, [%4], %5;\n"
      "add.u32 n, n, 1;\nand.pred p, p, q;\nand.pred p, p, r;\nsetp.lt.and.u32 c, n, " SPIN_LIMIT ", !p;\n@c bra.uni WAIT;\n}"
      :
      : "r"(a), "r"(pa), "r"(b), "r"(pb), "r"(d), "r"(pd)
      : "memory");
}
__device__ __forceinline__ void mbar_arrive_if(uint32_t bar, bool on) {
  asm volatile("{\n.reg .pred p;\nsetp.ne.u32 p, %1, 0;\n@p mbarrier.arrive.shared::cluster.b64 _, [%0];\n}" ::"r"(bar), "r"((uint32_t)on) : "memory");
}
__device__ __forceinline__ bool mbar_test(uint32_t bar, uint32_t parity) {
  uint32_t r;
  asm volatile("{\n.reg .pred p;\nmbarrier.test_wait.parity.shared::cta.b64 p, [%1], %2;\nselp.u32 %0, 1, 0, p;\n}"
               : "=r"(r) : "r"(bar), "r"(parity) : "memory");
  return r != 0;
}
__device__ __forceinline__ void poll_ge(const unsigned int* p, unsigned int target) {
  asm volatile(
      "{\n.reg .pred p, c;\n.reg .u32 n;\n.reg .s32 v;\nmov.u32 n, 0;\n"
      "POLL:\nld.relaxed.gpu.global.u32 v, [%0];\nsub.s32 v, v, %1;\nsetp.lt.s32 p, v, 0;\n"
      "add.u32 n, n, 1;\nsetp.lt.and.u32 c, n, " SPIN_LIMIT ", p;\n@c bra.uni POLL;\n}"
      :
      : "l"(p), "r"(target)
      : "memory");
}
__device__ __forceinline__ void signal_release(unsigned int* p, uint32_t v = 1) {
  asm volatile("red.release.gpu.global.add.u32 [%0], %1;" ::"l"(p), "r"(v) : "memory");
}
__device__ __forceinline__ void signal_relaxed(unsigned int* p, uint32_t v = 1) {
  asm volatile("red.relaxed.gpu.global.add.u32 [%0], %1;" ::"l"(p), "r"(v) : "memory");
}
__device__ __forceinline__ bool elect_one() {
  uint32_t pred;
  asm volatile("{\n.reg .pred p;\nelect.sync _|p, 0xffffffff;\nselp.u32 %0, 1, 0, p;\n}" : "=r"(pred));
  return pred != 0;
}
__device__ __forceinline__ void tma_load_2d(uint32_t dst, const CUtensorMap* map, uint32_t bar, int c0, int c1) {
  asm volatile(
      "cp.async.bulk.tensor.2d.shared::cluster.global.mbarrier::complete_tx::bytes [%0], [%1, {%3, %4}], [%2];" ::"r"(dst),
      "l"(map), "r"(bar), "r"(c0), "r"(c1)
      : "memory");
}
__device__ __forceinline__ void tma_load_3d(uint32_t dst, const CUtensorMap* map, uint32_t bar, int c0, int c1, int c2) {
  asm volatile(
      "cp.async.bulk.tensor.3d.shared::cluster.global.mbarrier::complete_tx::bytes [%0], [%1, {%3, %4, %5}], [%2];" ::"r"(dst),
      "l"(map), "r"(bar), "r"(c0), "r"(c1), "r"(c2)
      : "memory");
}
__device__ __forceinline__ void tma_load_3d_mc(uint32_t dst, const CUtensorMap* map, uint32_t bar, int c0, int c1, int c2) {
  asm volatile(
      "cp.async.bulk.tensor.3d.shared::cluster.global.mbarrier::complete_tx::bytes.multicast::cluster [%0], [%1, {%3, "
      "%4, %5}], [%2], %6;" ::"r"(dst),
      "l"(map), "r"(bar), "r"(c0), "r"(c1), "r"(c2), "h"((uint16_t)3)
      : "memory");
}
__device__ __forceinline__ void st_async_u4(uint32_t dst, uint32_t bar, uint32_t a, uint32_t b, uint32_t c, uint32_t d) {
  asm volatile("st.async.weak.shared::cluster.mbarrier::complete_tx::bytes.v4.b32 [%0], {%2, %3, %4, %5}, [%1];" ::"r"(dst),
               "r"(bar), "r"(a), "r"(b), "r"(c), "r"(d)
               : "memory");
}
__device__ __forceinline__ void tma_reduce_3d(const CUtensorMap* map, uint32_t src, int c0, int c1, int c2) {
  asm volatile("cp.reduce.async.bulk.tensor.3d.global.shared::cta.add.tile.bulk_group [%0, {%2, %3, %4}], [%1];" ::"l"(map),
               "r"(src), "r"(c0), "r"(c1), "r"(c2)
               : "memory");
}
__device__ __forceinline__ void tma_store_3d(const CUtensorMap* map, uint32_t src, int c0, int c1, int c2) {
  asm volatile("cp.async.bulk.tensor.3d.global.shared::cta.tile.bulk_group [%0, {%2, %3, %4}], [%1];" ::"l"(map), "r"(src),
               "r"(c0), "r"(c1), "r"(c2)
               : "memory");
}
__device__ __forceinline__ void tma_prefetch_2d(const CUtensorMap* map, int c0, int c1) {
  asm volatile("cp.async.bulk.prefetch.tensor.2d.L2.global.tile [%0, {%1, %2}];" ::"l"(map), "r"(c0), "r"(c1) : "memory");
}
__device__ __forceinline__ void prefetch_map(const CUtensorMap* map) {
  asm volatile("prefetch.tensormap [%0];" ::"l"(map) : "memory");
}
__device__ __forceinline__ void wgmma_fence() { asm volatile("wgmma.fence.sync.aligned;" ::: "memory"); }
__device__ __forceinline__ void wgmma_commit() { asm volatile("wgmma.commit_group.sync.aligned;" ::: "memory"); }
template <int N>
__device__ __forceinline__ void wgmma_wait() {
  asm volatile("wgmma.wait_group.sync.aligned %0;" ::"n"(N) : "memory");
}
__device__ __forceinline__ void named_bar_sync(int id, int nthreads) {
  asm volatile("bar.sync %0, %1;" ::"r"(id), "r"(nthreads) : "memory");
}
__device__ __forceinline__ void cluster_arrive_relaxed() { asm volatile("barrier.cluster.arrive.relaxed.aligned;" ::: "memory"); }
__device__ __forceinline__ void cluster_wait() { asm volatile("barrier.cluster.wait.acquire.aligned;" ::: "memory"); }
__device__ __forceinline__ uint32_t mapa(uint32_t addr, uint32_t rank) {
  uint32_t r;
  asm volatile("mapa.shared::cluster.u32 %0, %1, %2;" : "=r"(r) : "r"(addr), "r"(rank));
  return r;
}
__device__ __forceinline__ uint64_t desc_from_lo(uint32_t lo) { return (uint64_t)lo | (0x40000040ull << 32); }
__device__ __forceinline__ uint64_t desc_sbo(uint32_t lo, uint32_t sbo) { return (uint64_t)lo | ((0x40000000ull | (sbo >> 4)) << 32); }
__device__ __forceinline__ uint64_t desc_64(uint32_t lo) { return (uint64_t)lo | (0x80000020ull << 32); }
__device__ __forceinline__ uint32_t desc_lo_a(uint32_t addr) { return ((addr & 0x3FFFF) >> 4) | (1u << 16); }
__device__ __forceinline__ uint32_t desc_lo_b(uint32_t addr, uint32_t lbo_bytes) { return ((addr & 0x3FFFF) >> 4) | ((lbo_bytes >> 4) << 16); }
__device__ __forceinline__ uint32_t pack_bf16(float lo, float hi) {
  __nv_bfloat162 v = __floats2bfloat162_rn(lo, hi);
  return *reinterpret_cast<uint32_t*>(&v);
}
__device__ __forceinline__ float bf16r(float x) { return __uint_as_float(pack_bf16(0.f, x)); }
__device__ __forceinline__ float bf_lo(uint32_t u) { return __uint_as_float(u << 16); }
__device__ __forceinline__ float bf_hi(uint32_t u) { return __uint_as_float(u & 0xFFFF0000u); }
__device__ __forceinline__ uint4 lds_u4(uint32_t addr) {
  uint4 v;
  asm volatile("ld.shared.v4.b32 {%0, %1, %2, %3}, [%4];" : "=r"(v.x), "=r"(v.y), "=r"(v.z), "=r"(v.w) : "r"(addr) : "memory");
  return v;
}
__device__ __forceinline__ float2 lds_f2(uint32_t addr) {
  float2 v;
  asm volatile("ld.shared.v2.f32 {%0, %1}, [%2];" : "=f"(v.x), "=f"(v.y) : "r"(addr) : "memory");
  return v;
}
__device__ __forceinline__ void sts_f2(uint32_t addr, float a, float b) {
  asm volatile("st.shared.v2.f32 [%0], {%1, %2};" ::"r"(addr), "f"(a), "f"(b) : "memory");
}
__device__ __forceinline__ void sts_u4(uint32_t addr, uint32_t a, uint32_t b, uint32_t c, uint32_t d) {
  asm volatile("st.shared.v4.b32 [%0], {%1, %2, %3, %4};" ::"r"(addr), "r"(a), "r"(b), "r"(c), "r"(d) : "memory");
}
__device__ __forceinline__ void sts_u32(uint32_t addr, uint32_t v) { asm volatile("st.shared.b32 [%0], %1;" ::"r"(addr), "r"(v) : "memory"); }
__device__ __forceinline__ uint32_t lds_u32(uint32_t addr) {
  uint32_t v;
  asm volatile("ld.shared.b32 %0, [%1];" : "=r"(v) : "r"(addr) : "memory");
  return v;
}
__device__ __forceinline__ uint4 ldg_u4(const void* p, bool on = true) {
  uint4 v = make_uint4(0u, 0u, 0u, 0u);
  asm volatile("{\n.reg .pred p;\nsetp.ne.u32 p, %5, 0;\n@p ld.global.nc.L1::no_allocate.v4.b32 {%0, %1, %2, %3}, [%4];\n}"
               : "+r"(v.x), "+r"(v.y), "+r"(v.z), "+r"(v.w) : "l"(p), "r"((uint32_t)on) : "memory");
  return v;
}
__device__ __forceinline__ float4 ldg_cg_f4(const void* p) {
  float4 v;
  asm volatile("ld.global.cg.v4.f32 {%0, %1, %2, %3}, [%4];" : "=f"(v.x), "=f"(v.y), "=f"(v.z), "=f"(v.w) : "l"(p) : "memory");
  return v;
}
__device__ __forceinline__ void st_tagged(void* p, uint32_t a, uint32_t b, uint32_t c, uint32_t tag) {
  asm volatile("{\n.reg .b64 l, h;\n.reg .b128 v;\nmov.b64 l, {%1, %2};\nmov.b64 h, {%3, %4};\nmov.b128 v, {l, h};\n"
               "st.relaxed.gpu.global.b128 [%0], v;\n}" ::"l"(p), "r"(a), "r"(b), "r"(c), "r"(tag) : "memory");
}
__device__ __forceinline__ void st_tagged_any(uint64_t p, uint32_t a, uint32_t b, uint32_t c, uint32_t tag) {
  asm volatile("{\n.reg .b64 l, h;\n.reg .b128 v;\nmov.b64 l, {%1, %2};\nmov.b64 h, {%3, %4};\nmov.b128 v, {l, h};\n"
               "st.relaxed.gpu.b128 [%0], v;\n}" ::"l"(p), "r"(a), "r"(b), "r"(c), "r"(tag) : "memory");
}
__device__ __forceinline__ uint4 ld_tagged(const void* p) {
  uint4 r;
  asm volatile("{\n.reg .b64 l, h;\n.reg .b128 v;\nld.relaxed.gpu.global.b128 v, [%4];\nmov.b128 {l, h}, v;\n"
               "mov.b64 {%0, %1}, l;\nmov.b64 {%2, %3}, h;\n}" : "=r"(r.x), "=r"(r.y), "=r"(r.z), "=r"(r.w) : "l"(p) : "memory");
  return r;
}
__device__ __forceinline__ void cp_async16(uint32_t dst, const void* src) {
  asm volatile("cp.async.cg.shared.global [%0], [%1], 16;" ::"r"(dst), "l"(src) : "memory");
}
__device__ __forceinline__ void cp_async_arrive(uint32_t bar) {
  asm volatile("cp.async.mbarrier.arrive.shared::cta.b64 [%0];" ::"r"(bar) : "memory");
}
__device__ __forceinline__ void bulk_store(void* gdst, uint32_t src, uint32_t bytes) {
  asm volatile("cp.async.bulk.global.shared::cta.bulk_group [%0], [%1], %2;" ::"l"(gdst), "r"(src), "r"(bytes) : "memory");
}
__device__ __forceinline__ void bulk_load(uint32_t dst, const void* gsrc, uint32_t bytes, uint32_t bar) {
  asm volatile("cp.async.bulk.shared::cluster.global.mbarrier::complete_tx::bytes [%0], [%1], %2, [%3];" ::"r"(dst), "l"(gsrc),
               "r"(bytes), "r"(bar)
               : "memory");
}
__device__ __forceinline__ void bulk_commit() { asm volatile("cp.async.bulk.commit_group;" ::: "memory"); }
template <int N>
__device__ __forceinline__ void bulk_wait() { asm volatile("cp.async.bulk.wait_group %0;" ::"n"(N) : "memory"); }
__device__ __forceinline__ void stsm_x4(uint32_t addr, uint32_t a, uint32_t b, uint32_t c, uint32_t d) {
  asm volatile("stmatrix.sync.aligned.m8n8.x4.shared.b16 [%0], {%1, %2, %3, %4};" ::"r"(addr), "r"(a), "r"(b), "r"(c), "r"(d) : "memory");
}
__device__ __forceinline__ uint32_t movm(uint32_t a) {
  uint32_t d;
  asm volatile("movmatrix.sync.aligned.m8n8.trans.b16 %0, %1;" : "=r"(d) : "r"(a));
  return d;
}
__device__ __forceinline__ void mma_16816(float (&d)[4], uint32_t a0, uint32_t a1, uint32_t a2, uint32_t a3, uint32_t b0, uint32_t b1) {
  asm volatile("mma.sync.aligned.m16n8k16.row.col.f32.bf16.bf16.f32 {%0, %1, %2, %3}, {%4, %5, %6, %7}, {%8, %9}, {%0, %1, %2, %3};"
               : "+f"(d[0]), "+f"(d[1]), "+f"(d[2]), "+f"(d[3]) : "r"(a0), "r"(a1), "r"(a2), "r"(a3), "r"(b0), "r"(b1));
}
__device__ __forceinline__ void mma_16816_z(float (&d)[4], uint32_t a0, uint32_t a1, uint32_t a2, uint32_t a3, uint32_t b0, uint32_t b1) {
  asm volatile("mma.sync.aligned.m16n8k16.row.col.f32.bf16.bf16.f32 {%0, %1, %2, %3}, {%4, %5, %6, %7}, {%8, %9}, {%10, %10, %10, %10};"
               : "=f"(d[0]), "=f"(d[1]), "=f"(d[2]), "=f"(d[3]) : "r"(a0), "r"(a1), "r"(a2), "r"(a3), "r"(b0), "r"(b1), "f"(0.f));
}
__device__ __forceinline__ void mma_1688(float (&d)[4], uint32_t a0, uint32_t a1, uint32_t b0) {
  asm volatile("mma.sync.aligned.m16n8k8.row.col.f32.bf16.bf16.f32 {%0, %1, %2, %3}, {%4, %5}, {%6}, {%7, %7, %7, %7};"
               : "=f"(d[0]), "=f"(d[1]), "=f"(d[2]), "=f"(d[3]) : "r"(a0), "r"(a1), "r"(b0), "f"(0.f));
}
__device__ __forceinline__ void fence_proxy_async() { asm volatile("fence.proxy.async.shared::cta;" ::: "memory"); }

template<int N> __device__ __forceinline__ void wgmma_ss(float (&d)[N/2], uint64_t descA, uint64_t descB, int scaleD);
template<int N> __device__ __forceinline__ void wgmma_rs(float (&d)[N/2], uint32_t a0, uint32_t a1, uint32_t a2, uint32_t a3, uint64_t descB, int scaleD);
template<> __device__ __forceinline__ void wgmma_ss<64>(float (&d)[32], uint64_t descA, uint64_t descB, int scaleD) {
  asm volatile("{\n.reg .pred p;\nsetp.ne.b32 p, %34, 0;\n"
    "wgmma.mma_async.sync.aligned.m64n64k16.f32.bf16.bf16 {%0, %1, %2, %3, %4, %5, %6, %7, %8, %9, %10, %11, %12, %13, %14, %15, %16, %17, %18, %19, %20, %21, %22, %23, %24, %25, %26, %27, %28, %29, %30, %31}, %32, %33, p, 1, 1, 0, 1;\n}\n"
    : "+f"(d[0]), "+f"(d[1]), "+f"(d[2]), "+f"(d[3]), "+f"(d[4]), "+f"(d[5]), "+f"(d[6]), "+f"(d[7]), "+f"(d[8]), "+f"(d[9]), "+f"(d[10]), "+f"(d[11]), "+f"(d[12]), "+f"(d[13]), "+f"(d[14]), "+f"(d[15]), "+f"(d[16]), "+f"(d[17]), "+f"(d[18]), "+f"(d[19]), "+f"(d[20]), "+f"(d[21]), "+f"(d[22]), "+f"(d[23]), "+f"(d[24]), "+f"(d[25]), "+f"(d[26]), "+f"(d[27]), "+f"(d[28]), "+f"(d[29]), "+f"(d[30]), "+f"(d[31])
    : "l"(descA), "l"(descB), "r"(scaleD));
}
template<> __device__ __forceinline__ void wgmma_ss<128>(float (&d)[64], uint64_t descA, uint64_t descB, int scaleD) {
  asm volatile("{\n.reg .pred p;\nsetp.ne.b32 p, %66, 0;\n"
    "wgmma.mma_async.sync.aligned.m64n128k16.f32.bf16.bf16 {%0, %1, %2, %3, %4, %5, %6, %7, %8, %9, %10, %11, %12, %13, %14, %15, %16, %17, %18, %19, %20, %21, %22, %23, %24, %25, %26, %27, %28, %29, %30, %31, %32, %33, %34, %35, %36, %37, %38, %39, %40, %41, %42, %43, %44, %45, %46, %47, %48, %49, %50, %51, %52, %53, %54, %55, %56, %57, %58, %59, %60, %61, %62, %63}, %64, %65, p, 1, 1, 0, 1;\n}\n"
    : "+f"(d[0]), "+f"(d[1]), "+f"(d[2]), "+f"(d[3]), "+f"(d[4]), "+f"(d[5]), "+f"(d[6]), "+f"(d[7]), "+f"(d[8]), "+f"(d[9]), "+f"(d[10]), "+f"(d[11]), "+f"(d[12]), "+f"(d[13]), "+f"(d[14]), "+f"(d[15]), "+f"(d[16]), "+f"(d[17]), "+f"(d[18]), "+f"(d[19]), "+f"(d[20]), "+f"(d[21]), "+f"(d[22]), "+f"(d[23]), "+f"(d[24]), "+f"(d[25]), "+f"(d[26]), "+f"(d[27]), "+f"(d[28]), "+f"(d[29]), "+f"(d[30]), "+f"(d[31]), "+f"(d[32]), "+f"(d[33]), "+f"(d[34]), "+f"(d[35]), "+f"(d[36]), "+f"(d[37]), "+f"(d[38]), "+f"(d[39]), "+f"(d[40]), "+f"(d[41]), "+f"(d[42]), "+f"(d[43]), "+f"(d[44]), "+f"(d[45]), "+f"(d[46]), "+f"(d[47]), "+f"(d[48]), "+f"(d[49]), "+f"(d[50]), "+f"(d[51]), "+f"(d[52]), "+f"(d[53]), "+f"(d[54]), "+f"(d[55]), "+f"(d[56]), "+f"(d[57]), "+f"(d[58]), "+f"(d[59]), "+f"(d[60]), "+f"(d[61]), "+f"(d[62]), "+f"(d[63])
    : "l"(descA), "l"(descB), "r"(scaleD));
}
template<> __device__ __forceinline__ void wgmma_ss<216>(float (&d)[108], uint64_t descA, uint64_t descB, int scaleD) {
  asm volatile("{\n.reg .pred p;\nsetp.ne.b32 p, %110, 0;\n"
    "wgmma.mma_async.sync.aligned.m64n216k16.f32.bf16.bf16 {%0, %1, %2, %3, %4, %5, %6, %7, %8, %9, %10, %11, %12, %13, %14, %15, %16, %17, %18, %19, %20, %21, %22, %23, %24, %25, %26, %27, %28, %29, %30, %31, %32, %33, %34, %35, %36, %37, %38, %39, %40, %41, %42, %43, %44, %45, %46, %47, %48, %49, %50, %51, %52, %53, %54, %55, %56, %57, %58, %59, %60, %61, %62, %63, %64, %65, %66, %67, %68, %69, %70, %71, %72, %73, %74, %75, %76, %77, %78, %79, %80, %81, %82, %83, %84, %85, %86, %87, %88, %89, %90, %91, %92, %93, %94, %95, %96, %97, %98, %99, %100, %101, %102, %103, %104, %105, %106, %107}, %108, %109, p, 1, 1, 0, 1;\n}\n"
    : "+f"(d[0]), "+f"(d[1]), "+f"(d[2]), "+f"(d[3]), "+f"(d[4]), "+f"(d[5]), "+f"(d[6]), "+f"(d[7]), "+f"(d[8]), "+f"(d[9]), "+f"(d[10]), "+f"(d[11]), "+f"(d[12]), "+f"(d[13]), "+f"(d[14]), "+f"(d[15]), "+f"(d[16]), "+f"(d[17]), "+f"(d[18]), "+f"(d[19]), "+f"(d[20]), "+f"(d[21]), "+f"(d[22]), "+f"(d[23]), "+f"(d[24]), "+f"(d[25]), "+f"(d[26]), "+f"(d[27]), "+f"(d[28]), "+f"(d[29]), "+f"(d[30]), "+f"(d[31]), "+f"(d[32]), "+f"(d[33]), "+f"(d[34]), "+f"(d[35]), "+f"(d[36]), "+f"(d[37]), "+f"(d[38]), "+f"(d[39]), "+f"(d[40]), "+f"(d[41]), "+f"(d[42]), "+f"(d[43]), "+f"(d[44]), "+f"(d[45]), "+f"(d[46]), "+f"(d[47]), "+f"(d[48]), "+f"(d[49]), "+f"(d[50]), "+f"(d[51]), "+f"(d[52]), "+f"(d[53]), "+f"(d[54]), "+f"(d[55]), "+f"(d[56]), "+f"(d[57]), "+f"(d[58]), "+f"(d[59]), "+f"(d[60]), "+f"(d[61]), "+f"(d[62]), "+f"(d[63]), "+f"(d[64]), "+f"(d[65]), "+f"(d[66]), "+f"(d[67]), "+f"(d[68]), "+f"(d[69]), "+f"(d[70]), "+f"(d[71]), "+f"(d[72]), "+f"(d[73]), "+f"(d[74]), "+f"(d[75]), "+f"(d[76]), "+f"(d[77]), "+f"(d[78]), "+f"(d[79]), "+f"(d[80]), "+f"(d[81]), "+f"(d[82]), "+f"(d[83]), "+f"(d[84]), "+f"(d[85]), "+f"(d[86]), "+f"(d[87]), "+f"(d[88]), "+f"(d[89]), "+f"(d[90]), "+f"(d[91]), "+f"(d[92]), "+f"(d[93]), "+f"(d[94]), "+f"(d[95]), "+f"(d[96]), "+f"(d[97]), "+f"(d[98]), "+f"(d[99]), "+f"(d[100]), "+f"(d[101]), "+f"(d[102]), "+f"(d[103]), "+f"(d[104]), "+f"(d[105]), "+f"(d[106]), "+f"(d[107])
    : "l"(descA), "l"(descB), "r"(scaleD));
}
template<> __device__ __forceinline__ void wgmma_rs<64>(float (&d)[32], uint32_t a0, uint32_t a1, uint32_t a2, uint32_t a3, uint64_t descB, int scaleD) {
  asm volatile("{\n.reg .pred p;\nsetp.ne.b32 p, %37, 0;\n"
    "wgmma.mma_async.sync.aligned.m64n64k16.f32.bf16.bf16 {%0, %1, %2, %3, %4, %5, %6, %7, %8, %9, %10, %11, %12, %13, %14, %15, %16, %17, %18, %19, %20, %21, %22, %23, %24, %25, %26, %27, %28, %29, %30, %31}, {%32, %33, %34, %35}, %36, p, 1, 1, 1;\n}\n"
    : "+f"(d[0]), "+f"(d[1]), "+f"(d[2]), "+f"(d[3]), "+f"(d[4]), "+f"(d[5]), "+f"(d[6]), "+f"(d[7]), "+f"(d[8]), "+f"(d[9]), "+f"(d[10]), "+f"(d[11]), "+f"(d[12]), "+f"(d[13]), "+f"(d[14]), "+f"(d[15]), "+f"(d[16]), "+f"(d[17]), "+f"(d[18]), "+f"(d[19]), "+f"(d[20]), "+f"(d[21]), "+f"(d[22]), "+f"(d[23]), "+f"(d[24]), "+f"(d[25]), "+f"(d[26]), "+f"(d[27]), "+f"(d[28]), "+f"(d[29]), "+f"(d[30]), "+f"(d[31])
    : "r"(a0), "r"(a1), "r"(a2), "r"(a3), "l"(descB), "r"(scaleD));
}
template<> __device__ __forceinline__ void wgmma_rs<216>(float (&d)[108], uint32_t a0, uint32_t a1, uint32_t a2, uint32_t a3, uint64_t descB, int scaleD) {
  asm volatile("{\n.reg .pred p;\nsetp.ne.b32 p, %113, 0;\n"
    "wgmma.mma_async.sync.aligned.m64n216k16.f32.bf16.bf16 {%0, %1, %2, %3, %4, %5, %6, %7, %8, %9, %10, %11, %12, %13, %14, %15, %16, %17, %18, %19, %20, %21, %22, %23, %24, %25, %26, %27, %28, %29, %30, %31, %32, %33, %34, %35, %36, %37, %38, %39, %40, %41, %42, %43, %44, %45, %46, %47, %48, %49, %50, %51, %52, %53, %54, %55, %56, %57, %58, %59, %60, %61, %62, %63, %64, %65, %66, %67, %68, %69, %70, %71, %72, %73, %74, %75, %76, %77, %78, %79, %80, %81, %82, %83, %84, %85, %86, %87, %88, %89, %90, %91, %92, %93, %94, %95, %96, %97, %98, %99, %100, %101, %102, %103, %104, %105, %106, %107}, {%108, %109, %110, %111}, %112, p, 1, 1, 1;\n}\n"
    : "+f"(d[0]), "+f"(d[1]), "+f"(d[2]), "+f"(d[3]), "+f"(d[4]), "+f"(d[5]), "+f"(d[6]), "+f"(d[7]), "+f"(d[8]), "+f"(d[9]), "+f"(d[10]), "+f"(d[11]), "+f"(d[12]), "+f"(d[13]), "+f"(d[14]), "+f"(d[15]), "+f"(d[16]), "+f"(d[17]), "+f"(d[18]), "+f"(d[19]), "+f"(d[20]), "+f"(d[21]), "+f"(d[22]), "+f"(d[23]), "+f"(d[24]), "+f"(d[25]), "+f"(d[26]), "+f"(d[27]), "+f"(d[28]), "+f"(d[29]), "+f"(d[30]), "+f"(d[31]), "+f"(d[32]), "+f"(d[33]), "+f"(d[34]), "+f"(d[35]), "+f"(d[36]), "+f"(d[37]), "+f"(d[38]), "+f"(d[39]), "+f"(d[40]), "+f"(d[41]), "+f"(d[42]), "+f"(d[43]), "+f"(d[44]), "+f"(d[45]), "+f"(d[46]), "+f"(d[47]), "+f"(d[48]), "+f"(d[49]), "+f"(d[50]), "+f"(d[51]), "+f"(d[52]), "+f"(d[53]), "+f"(d[54]), "+f"(d[55]), "+f"(d[56]), "+f"(d[57]), "+f"(d[58]), "+f"(d[59]), "+f"(d[60]), "+f"(d[61]), "+f"(d[62]), "+f"(d[63]), "+f"(d[64]), "+f"(d[65]), "+f"(d[66]), "+f"(d[67]), "+f"(d[68]), "+f"(d[69]), "+f"(d[70]), "+f"(d[71]), "+f"(d[72]), "+f"(d[73]), "+f"(d[74]), "+f"(d[75]), "+f"(d[76]), "+f"(d[77]), "+f"(d[78]), "+f"(d[79]), "+f"(d[80]), "+f"(d[81]), "+f"(d[82]), "+f"(d[83]), "+f"(d[84]), "+f"(d[85]), "+f"(d[86]), "+f"(d[87]), "+f"(d[88]), "+f"(d[89]), "+f"(d[90]), "+f"(d[91]), "+f"(d[92]), "+f"(d[93]), "+f"(d[94]), "+f"(d[95]), "+f"(d[96]), "+f"(d[97]), "+f"(d[98]), "+f"(d[99]), "+f"(d[100]), "+f"(d[101]), "+f"(d[102]), "+f"(d[103]), "+f"(d[104]), "+f"(d[105]), "+f"(d[106]), "+f"(d[107])
    : "r"(a0), "r"(a1), "r"(a2), "r"(a3), "l"(descB), "r"(scaleD));
}

constexpr int TILE = 8192, HALF = 9 * TILE;
constexpr int SLOT = 16384;
constexpr int RING = 2 * HALF;
constexpr int OVF = RING + 5 * SLOT;
constexpr int TAB = OVF + 1024;
constexpr int BARS = TAB + 1024;
constexpr int SMEM_BYTES = BARS + 1024;
constexpr int WOA = 9216;
constexpr int B_FULL = BARS, B_FX = BARS + 56, B_AUX = BARS + 200, B_NB = BARS + 208, B_ROLE = BARS + 272, B_S1 = BARS + 280,
              B_ST = BARS + 288, B_EMPTY = BARS + 432, B_J = BARS + 488, B_XF = BARS + 496,
              B_QK = BARS + 504, B_RX = BARS + 512, B_SR = BARS + 528, B_OX = BARS + 536, B_HP = BARS + 552;
constexpr int S_ROLE = BARS + 568, S_EP = BARS + 572, S_WS = BARS + 576;

template <int V>
struct IC {
  static constexpr int value = V;
};
struct Maps {
  CUtensorMap x0, r, wq, wo, wg, wu, wd, tg, tu, hg, hu;
};

#define TA0(i)
#define TA(i)
#define TS(i)
#define TR(i)

__device__ __forceinline__ int tid_now() {
  int t;
  asm volatile("mov.u32 %0, %%tid.x;" : "=r"(t));
  return t;
}
__device__ __forceinline__ float quad_sum(float v) {
  v += __shfl_xor_sync(0xffffffffu, v, 1);
  return v + __shfl_xor_sync(0xffffffffu, v, 2);
}
__device__ __forceinline__ float inv_sd(float var) {
  float s, r;
  asm("sqrt.approx.ftz.f32 %0, %1;" : "=f"(s) : "f"(bf16r(bf16r(fmaxf(var, 0.f)) + 1e-5f)));
  asm("rcp.approx.ftz.f32 %0, %1;" : "=f"(r) : "f"(bf16r(s)));
  return r;
}
__device__ __forceinline__ float sum8(const uint4& v) {
  return ((bf_lo(v.x) + bf_hi(v.x)) + (bf_lo(v.y) + bf_hi(v.y))) + ((bf_lo(v.z) + bf_hi(v.z)) + (bf_lo(v.w) + bf_hi(v.w)));
}
__device__ __forceinline__ void warp_arrive(uint32_t bar) {
  __syncwarp();
  if ((tid_now() & 31) == 0) mbar_arrive(bar);
}
__device__ __forceinline__ void release_slot(uint32_t sb, int p, bool on = true) {
  asm volatile("{\n.reg .pred p;\nsetp.eq.u32 p, %1, 0;\n@p mbarrier.arrive.shared::cta.b64 _, [%0];\n}" ::"r"(sb + B_EMPTY + 8 * p),
               "r"((tid_now() & 31) | (on ? 0 : 1))
               : "memory");
}
__device__ __forceinline__ uint32_t stage_addr(uint32_t sb) {
  const int tid = tid_now(), lane = tid & 31;
  return sb + (tid >> 7) * HALF + ((tid >> 5) & 3) * 2048 + (lane & 15) * 128 + (((lane >> 4) ^ (lane & 7)) << 4);
}
__device__ __forceinline__ void stage_done(uint32_t sb, int a, int n) {
    __syncwarp();
  const int tid = tid_now();
  if ((tid & 31) < n) mbar_arrive(sb + B_ST + 72 * (tid >> 7) + 8 * (a + (tid & 31)));
}
template <int I0 = 0, int I1 = 4>
__device__ __forceinline__ void stage_tile(const float (&acc)[32], float m0, float c0, float m1, float c1, uint32_t sb, int a, int b, int n) {
  const uint32_t ad = stage_addr(sb) + a * TILE;
#pragma unroll
  for (int i = I0; i < I1; ++i)
    stsm_x4(ad ^ (i << 5), pack_bf16(fmaf(acc[8 * i], m0, c0), fmaf(acc[8 * i + 1], m0, c0)),
            pack_bf16(fmaf(acc[8 * i + 2], m1, c1), fmaf(acc[8 * i + 3], m1, c1)),
            pack_bf16(fmaf(acc[8 * i + 4], m0, c0), fmaf(acc[8 * i + 5], m0, c0)),
            pack_bf16(fmaf(acc[8 * i + 6], m1, c1), fmaf(acc[8 * i + 7], m1, c1)));
  if (n) stage_done(sb, b, n);
}

#define NLAYERS 2
#define X_EARLY 2
#define X_SCHED 0x1111111ull
#define PACE 2800
#define X_PF 0
#define DN_LATE 0
#define ST_END 5
#define GU_PF0 16
#define GU_PFN 16
#define R0_N 0
#define R1_N 2
#define PACE_R 1400
#define PACE0 4200
#define IMG 1
#define GU_PRE 1
#define Q_H 8
#define LAZY 2
#define Q_ST0 7
#define KH 4
#define H_DELAY 4000
#define H_SLEEP 100
#define PFM 1
#define T_HOLD 8
#define T_LEAD 8
#define Q_ST1 6

__global__ void __cluster_dims__(2, 1, 1) __launch_bounds__(384, 1)
mega_kernel(const __grid_constant__ Maps mp, const __nv_bfloat16* __restrict__ x0, const __nv_bfloat16* __restrict__ wqkv,
            const __nv_bfloat16* __restrict__ wo, __nv_bfloat16* __restrict__ out, int small_gpc) {
  extern __shared__ __align__(1024) uint8_t smem[];
  const uint32_t sb = smem_u32(smem);
  const uint32_t rank = blockIdx.x & 1;
  const int warp = __shfl_sync(0xffffffffu, threadIdx.x >> 5, 0);
  TA0(63);
  if (warp != 8) {
    if (elect_one()) {
      const uint32_t b0 = sb + BARS + 48 * (warp - (warp > 8));
      if (warp < 11) {
#pragma unroll
        for (int i = 0; i < 6; ++i) mbar_init(b0 + 8 * i, warp < 6 ? 1 : warp < 10 ? 4 : 8);
        if (warp == 5) mbar_expect_tx(sb + B_ROLE, 4);
      } else {
#pragma unroll
        for (int i = 0; i < 11; ++i) mbar_init(b0 + 8 * i, i < 3 ? 8 : i < 6 ? 4 : i < 7 ? 2 : 1);
      }
      asm volatile("fence.mbarrier_init.release.cluster;" ::: "memory");
      if (warp == 9) prefetch_map(&mp.x0);
      if (warp == 10) prefetch_map(&mp.wq);
    }
  }
  __syncwarp();
  cluster_arrive_relaxed();
  uint32_t pr, ep1 = 0;
  asm volatile("mov.u32 %0, %%smid;" : "=r"(pr));
  pr >>= 1;
  pr = !small_gpc ? (pr < 64 ? pr & 7 : 8) : pr < 32 ? pr & 7 : pr < 60 ? 1 + (pr - 32) % 7 : pr < 62 ? 8 : 0;
  asm volatile("{\n.reg .pred p, q;\nsetp.eq.u32 p, %3, 256;\nsetp.ge.u32 q, %3, 288;\n"
               "@p atom.relaxed.gpu.global.inc.u32 %0, [%1], 0x7fffffff;\n@q ld.relaxed.gpu.global.u32 %0, [%2];\n}"
               : "+r"(ep1)
               : "l"(&gs_.claim[pr]), "l"(&gs_.epoch[blockIdx.x]), "r"(threadIdx.x | rank)
               : "memory");
  TA0(2);

  if (warp >= 8) {
    asm volatile("setmaxnreg.dec.sync.aligned.u32 24;");
    int j, rb;
    auto start = [&]() {
      mbar_wait(sb + B_ROLE, 0);
      const int role = __shfl_sync(0xffffffffu, lds_u32(sb + S_ROLE), 0);
      j = (role & 3) * 2 + rank;
      rb = role >> 2;
      ep1 = __shfl_sync(0xffffffffu, ep1, 0) + 1;
      TA0(59);
    };
    auto load_wq = [&](uint32_t dst, uint32_t bar, int s) {
      const int lane = tid_now() & 31;
      const __nv_bfloat16* src = wqkv + (32 * s + lane) * NQKV + 72 * j + (rank ? 0 : 64);
      if (elect_one()) tma_load_3d(dst, &mp.wq, bar, 72 * j + 8 * rank, 32 * s, 0);
#pragma unroll
      for (int c = 0; c < 3; ++c) cp_async16(dst + 12288 + lane * 128 + ((c ^ (lane & 7)) << 4), src + c * 576);
      cp_async_arrive(bar);
      __syncwarp();
      if (elect_one()) mbar_expect_tx(bar, 12288);
    };
    auto load_halves = [&](uint32_t dst, uint32_t bar, int c0, int c1, int cy) {
      if (elect_one()) tma_load_2d(dst, &mp.hg, bar, c0, cy);
      if (elect_one()) tma_load_2d(dst + 4096, &mp.hg, bar, c1, cy);
      if (elect_one()) tma_load_2d(dst + 8192, &mp.hu, bar, c0, cy);
      if (elect_one()) tma_load_2d(dst + 12288, &mp.hu, bar, c1, cy);
    };
    auto publish = [&](bool tell) {
      sts_u32(sb + S_EP, ep1);
      TA0(10);
        const int lane = tid_now() & 31;
        mbar_wait(sb + B_J, 0);
        float2 c = make_float2(0.f, 0.f);
#pragma unroll
        for (int w = 0; w < 8; ++w) {
          const float2 v = lds_f2(sb + OVF + w * 256 + lane * 8);
          c.x += v.x;
          c.y += v.y;
        }
        if (blockIdx.x < 108) *reinterpret_cast<float2*>(gs_.csq + (blockIdx.x & 3) * NQKV + (blockIdx.x >> 2) * 64 + 2 * lane) = c;
        if (tell) asm volatile("bar.arrive 6, 96;" ::: "memory");
        if (elect_one()) signal_release(&gs_.flag[FL_J]);
        TA0(11);
        poll_ge(&gs_.flag[FL_J], ep1 * NCTA);
        TA0(12);
        if (blockIdx.x == 0 && lane < 9) gs_.claim[lane] = 0u;
    };
    if (warp == 8) {
      cluster_wait();
      if (rank == 0) {
        uint32_t claim = __shfl_sync(0xffffffffu, ep1, 0);
#pragma unroll 1
        for (int i = 0; i < 8 && claim >= (pr == 8 ? 2 : 8); ++i) {
          pr = pr == 8 ? 0 : pr + 1;
          if (tid_now() == 256) asm volatile("atom.relaxed.gpu.global.inc.u32 %0, [%1], 0x7fffffff;" : "=r"(claim) : "l"(&gs_.claim[pr]) : "memory");
          claim = __shfl_sync(0xffffffffu, claim, 0);
        }
        claim = ((pr >> 2) * 8 + (claim & 7)) * 4 + (pr & 3);
        const uint32_t r = tid_now() & 31;
        if (r < 2)
          asm volatile("st.async.weak.shared::cluster.mbarrier::complete_tx::bytes.u32 [%0], %1, [%2];" ::"r"(mapa(sb + S_ROLE, r)),
                       "r"(claim), "r"(mapa(sb + B_ROLE, r))
                       : "memory");
        __syncwarp();
      }
      start();
      if (rb >= 16) {
        int p = 2;
        uint32_t ph = 1;
        named_bar_sync(6, 96);
#pragma unroll 1
        for (int n = 0, s = 0; n < 72 * NLAYERS; ++n) {
          const uint32_t bar = sb + B_FULL + 8 * p;
          mbar_wait(bar + (B_EMPTY - B_FULL), ph);
          if (elect_one()) {
            bulk_load(sb + RING + p * SLOT, gs_.himg + s * 1024, SLOT, bar);
            mbar_expect_tx(bar, SLOT);
          }
          if (n % 72 < 26) s += s < 18 ? 9 : -17;
          else if (++s == 36) s = 0;
          if (++p == 5) p = 0;
          if (p == 2) ph ^= 1;
        }
      } else {
      int p = 2;
      uint32_t ph = 1;
      const int f0 = j * 576;
      int xi = X_EARLY;
#pragma unroll 1
      for (int L = 0; L < NLAYERS; ++L) {
#pragma unroll 1
        for (int s = 0; s < 18; ++s) {
          const uint32_t bar = sb + B_FULL + 8 * p;
          mbar_wait(bar + (B_EMPTY - B_FULL), ph);
          TR(s);
          if (L == 0 || !IMG) {
            load_wq(sb + RING + p * SLOT, bar, s);
            if (L == 0 && elect_one()) {
#pragma unroll 1
              for (int e = (X_SCHED >> (2 * s)) & 3; e > 0; --e, ++xi)
                tma_load_3d_mc(sb + rank * HALF + xi * TILE, &mp.x0, sb + B_FX + 72 * rank + 8 * xi, xi * 64, rb * 64 + rank * 32, 0);
              const int u = (s - GU_PF0) * 8 + (rb >> 1);
              if (s >= GU_PF0 && u < GU_PFN) tma_prefetch_2d((rb & 1) ? &mp.wu : &mp.wg, f0 + 64 * (u % 3), 64 * (u / 3));
            }
          } else if (elect_one()) {
            bulk_load(sb + RING + p * SLOT, gs_.wimg + (j * 18 + s) * 1024, SLOT, bar);
            mbar_expect_tx(bar, SLOT);
          }
          if (++p == 5) p = 0;
          if (p == 2) ph ^= 1;
        }
#pragma unroll 1
        for (int s = 0; s < 5; ++s) {
          const int cx = s ? 64 * (2 * s - 1 + rank) : 0;
          mbar_wait(sb + B_EMPTY + 8 * s, ph);
          if (elect_one()) {
            if (s) tma_load_2d(sb + RING + (2 * s - 1) * WOA, &mp.wo, sb + B_FULL + 8 * s, cx, 72 * j);
            tma_load_2d(sb + RING + 2 * s * WOA, &mp.wo, sb + B_FULL + 8 * s, cx, 72 * (s ? j ^ 1 : j));
            mbar_expect_tx(sb + B_FULL + 8 * s, s ? 2 * WOA : WOA);
          }
          if (s == 1) ph ^= 1;
        }
        {
          int cx = f0, cy = 0;
          if (PFM && elect_one()) {
            prefetch_map(&mp.tg);
            prefetch_map(&mp.tu);
            prefetch_map(&mp.wd);
          }
#pragma unroll 1
          for (int n = 0; n < 72; ++n) {
            const uint32_t dst = sb + RING + p * SLOT, bar = sb + B_FULL + 8 * p;
            if (n == (rank ? R1_N : R0_N)) {
              mbar_wait(sb + B_ST + 72 + 8, 0);
              fence_proxy_async();
              if (elect_one()) tma_reduce_3d(&mp.r, sb + HALF + (1 + rank) * TILE, 64 + 64 * rank, rb * 64 + 32, 0);
              bulk_commit();
              if (!rank) {
                bulk_wait<0>();
                asm volatile("bar.arrive 8, 64;" ::: "memory");
              }
              mbar_wait(sb + B_ST + 8, 0);
              fence_proxy_async();
              if (elect_one()) tma_reduce_3d(&mp.r, sb + (1 + rank) * TILE, 64 + 64 * rank, rb * 64, 0);
              bulk_commit();
            }
            mbar_wait(bar + (B_EMPTY - B_FULL), ph);
            if (elect_one()) tma_load_2d(dst, &mp.wg, bar, cx, cy);
            if (elect_one()) tma_load_2d(dst + 8192, &mp.wu, bar, cx, cy);
            if (elect_one()) mbar_expect_tx(bar, 16384);
            if (n == (rank ? R1_N : R0_N)) {
              bulk_wait<0>();
              if (rank) asm volatile("bar.arrive 8, 64;" ::: "memory");
              asm volatile("bar.arrive 7, 64;" ::: "memory");
            }
            if (n < 26) {
              cx += 64;
              if (cx == f0 + 192) {
                cx = f0;
                cy += 64;
              }
            } else if ((cy += 64) == 576) {
              cy = 0;
              cx += 64;
            }
            if (++p == 5) p = 0;
            if (p == 2) ph ^= 1;
          }
        }
#pragma unroll 1
        for (int cy = 0; cy < 576; cy += 64) {
          const uint32_t dst = sb + RING + p * SLOT, bar = sb + B_FULL + 8 * p;
          mbar_wait(bar + (B_EMPTY - B_FULL), ph);
          if (elect_one()) tma_load_3d(dst, &mp.tg, bar, 0, cy, 18 * j + 16);
          if (elect_one()) tma_load_3d(dst + 8192, &mp.tu, bar, 0, cy, 18 * j + 16);
          if (elect_one()) mbar_expect_tx(bar, 16384);
          if (++p == 5) p = 0;
          if (p == 2) ph ^= 1;
        }
        {
          int cx = 0, cy = f0;
#pragma unroll 1
          for (int n = 35; n > -6; --n) {
            const uint32_t dst = p < 5 ? sb + RING + p * SLOT : sb + 2 * TILE + p * TILE, bar = sb + B_FULL + 8 * p;
            mbar_wait(bar + (B_EMPTY - B_FULL), ph);
            if (elect_one()) tma_load_2d(dst, &mp.wd, bar, cx, cy);
            if ((cy += 64) == f0 + 576) {
              cy = f0;
              cx += 64;
            }
            if (n > -5 && elect_one()) tma_load_2d(dst + (p < 5 ? 8192 : HALF), &mp.wd, bar, cx, cy);
            if (elect_one()) mbar_expect_tx(bar, n > -5 ? 16384 : 8192);
            if ((cy += 64) == f0 + 576) {
              cy = f0;
              cx += 64;
            }
            if (IMG && n == 8 && L + 1 < NLAYERS) poll_ge(&gs_.flag[FL_W + j], lds_u32(sb + S_EP) * 18u);
            if (++p == (n > 1 ? 7 : 5)) p = 0;
            if (p == 2) ph ^= 1;
          }
        }
      }
      }
    } else if (warp == 9) {
      cluster_wait();
      start();
      if (rb >= 16) {
        publish(false);
        named_bar_sync(6, 96);
#pragma unroll 1
        for (int n = 0; n < 2 * NLAYERS; ++n) {
          const int lane = min(tid_now() & 31, 17), w = lane >= 9, r = (rb - 16) * 8 + rank * 4 + (n & 1) * 2 + w;
          const unsigned int* fl = &gs_.flag[(n >> 1) * 1024 + r * 32 + 16 + lane - 9 * w];
          uint32_t todo = 0x3FFFFu;
#pragma unroll 1
          for (int it = 0; todo && it < SPIN_MAX; ++it) {
            unsigned int v;
            asm volatile("ld.relaxed.gpu.global.u32 %0, [%1];" : "=r"(v) : "l"(fl) : "memory");
            const uint32_t ready =
                __ballot_sync(0xffffffffu, (int)(v - ep1 * 8u) >= 0 && mbar_test(sb + B_ST + 8 * lane, ~n & 1)) & todo;
            todo &= ~ready;
            if ((ready >> (tid_now() & 31)) & 1) {
              mbar_expect_tx(sb + B_FX + 8 * lane, TILE);
              tma_load_3d(sb + lane * TILE, &mp.r, sb + B_FX + 8 * lane, (lane - 9 * w) * 64, r * 64 + 32, 0);
            }
            __syncwarp();
            if (H_SLEEP && todo == 0x3FFFFu) __nanosleep(H_SLEEP);
          }
        }
        if (elect_one()) gs_.epoch[blockIdx.x] = ep1;
      } else {
      auto fetch = [&](const CUtensorMap* map, uint32_t mask) {
        const int lane = tid_now() & 31;
        if ((mask >> lane) & 1)
          tma_load_3d_mc(sb + rank * HALF + lane * TILE, map, sb + B_FX + 72 * rank + 8 * lane, lane * 64, rb * 64 + rank * 32, 0);
        __syncwarp();
      };
      if ((tid_now() & 31) < 18) mbar_expect_tx(sb + B_FX + 8 * (tid_now() & 31), TILE);
      fetch(&mp.x0, (1u << X_EARLY) - 1);
      publish(true);
      {
        const int lane = tid_now() & 31;
        if (lane < 18) {
          const float4 w = ldg_cg_f4(gs_.wsum + 72 * j + 4 * lane);
          sts_u4(sb + S_WS + lane * 16, __float_as_uint(w.x), __float_as_uint(w.y), __float_as_uint(w.z), __float_as_uint(w.w));
        }
      }
#pragma unroll 1
      for (int n = 0; n < 2 * NLAYERS - 1; ++n) {
        if (n < NLAYERS) {
#pragma unroll 1
          for (int c = tid_now() & 31; c < 54; c += 32) {
            const int part = c / 18, i = c - 18 * part;
            const float* src = gs_.csq + part * 576 + 72 * j + 4 * (rank ? (i + 2) % 18 : i);
            float4 a = ldg_cg_f4(src), b = ldg_cg_f4(src + NQKV), d = ldg_cg_f4(src + 2 * NQKV);
            a.x += b.x; a.y += b.y; a.z += b.z; a.w += b.w;
            b = ldg_cg_f4(src + 3 * NQKV);
            a.x += b.x + d.x; a.y += b.y + d.y; a.z += b.z + d.z; a.w += b.w + d.w;
            const uint32_t h0 = pack_bf16(a.x, a.y), h1 = pack_bf16(a.z, a.w);
            const uint32_t ad = (i < 16 ? part * 256 + (((i >> 1) ^ (2 * part)) << 4) : 768 + ((part ^ 6) << 4)) + (i & 1) * 8;
            sts_f2(sb + OVF + ad, __uint_as_float(h0), __uint_as_float(h1));
            sts_f2(sb + OVF + (ad ^ 144), __uint_as_float(pack_bf16(a.x - bf_lo(h0), a.y - bf_hi(h0))),
                   __uint_as_float(pack_bf16(a.z - bf_lo(h1), a.w - bf_hi(h1))));
          }
          const int lane = tid_now() & 31;
          if (lane < 10) sts_u4(sb + OVF + 768 + (lane & 1) * 128 + (((3 + (lane >> 1)) ^ 6 ^ (lane & 1)) << 4), 0u, 0u, 0u, 0u);
          fence_proxy_async();
          warp_arrive(sb + B_AUX);
        }
        {
          const int lane = tid_now() & 31;
          const uint32_t bar = sb + B_FX + 8 * min(lane, 17);
#pragma unroll 1
          for (int it = 0; it < SPIN_MAX; ++it)
            if (__all_sync(0xffffffffu, mbar_test(bar, n & 1))) break;
          if (lane < 18) mbar_expect_tx(bar, TILE);
        }
        const unsigned int* fl = &gs_.flag[n * 512 + rb * 32 + rank * 16 + (tid_now() & 15)];
        if (LAZY) mbar_wait(sb + B_ST + 72 * rank, n & 1);
        uint32_t todo = 0x1FFu;
#pragma unroll 1
        for (int it = 0; todo && it < SPIN_MAX; ++it) {
          unsigned int v;
          asm volatile("ld.relaxed.gpu.global.u32 %0, [%1];" : "=r"(v) : "l"(fl) : "memory");
          const uint32_t ready = __ballot_sync(0xffffffffu, (int)(v - ep1 * 8u) >= 0) & todo;
          if (LAZY > 1 && (n & 1) && !ready && (todo & 0x7F)) __nanosleep(300);
          if (ready) {
            todo &= ~ready;
            fetch(&mp.r, ready);
          }
        }
      }
      uint32_t bid;
      asm volatile("mov.u32 %0, %%ctaid.x;" : "=r"(bid));
      if (elect_one()) gs_.epoch[bid] = ep1;
      }
    } else {
      cluster_wait();
      start();
      if (rb >= 16) {
      if (warp == 10) {
        const int t = (rb - 16) * 2 + rank;
        __nanosleep(H_DELAY);
#pragma unroll 1
        for (int kb = 0; kb < 11; ++kb) {
          if (kb < 9) {
            load_halves(sb + kb * SLOT, sb + B_NB + 8 * (kb & 3), 544 + 1152 * t, 1120 + 1152 * t, 64 * kb);
            if (elect_one()) mbar_expect_tx(sb + B_NB + 8 * (kb & 3), SLOT);
          }
          if (kb >= 2) {
            mbar_wait(sb + B_NB + 8 * ((kb - 2) & 3), ((kb - 2) >> 2) & 1);
            if (elect_one()) bulk_store(gs_.himg + (t * 9 + kb - 2) * 1024, sb + (kb - 2) * SLOT, SLOT);
          }
        }
        bulk_commit();
        bulk_wait<0>();
        if (elect_one()) signal_release(&gs_.flag[FL_W + 8]);
        poll_ge(&gs_.flag[FL_W + 8], ep1 * 4u);
        asm volatile("bar.arrive 6, 96;" ::: "memory");
      }
      } else {
      const int h = warp & 1;
      if (h) {
        const int lane = tid_now() & 31;
#pragma unroll 1
        for (int i = 0; i < 12; ++i) st_tagged(gs_.halo + (rb * 8 + j) * 384 + i * 32 + lane, 0u, 0u, 0u, 2 * ep1 - 1);
        if (lane < 16) st_tagged(gs_.stat + rb * 128 + (lane >> 3) * 64 + 8 * j + (lane & 7), 0u, 0u, 0u, 4 * ep1 - 1);
      }

      auto copy = [&](int hh, int c) {
        if (elect_one()) tma_store_3d(&mp.r, sb + hh * HALF + c * TILE, 64 * c, rb * 64 + hh * 32, 0);
        bulk_commit();
        bulk_wait<0>();
        __syncwarp();
        if (c < 3) asm volatile("fence.acq_rel.gpu;" ::: "memory");
      };
      float s1 = 0.f, s2 = 0.f;
      int kb = 0;
      uint32_t hn = 0;
      auto tile_stats = [&]() {
        const int lane = tid_now() & 31;
        const uint32_t ad = sb + h * HALF + kb * TILE + j * 1024 + (lane & 28) * 32 + (lane & 7) * 16;
        const uint4 u = lds_u4(ad), v = lds_u4(ad ^ 64);
        const uint32_t w[8] = {u.x, u.y, u.z, u.w, v.x, v.y, v.z, v.w};
        float a = 0.f, b = 0.f;
#pragma unroll
        for (int e = 0; e < 8; ++e) {
          const float lo = bf_lo(w[e]), hi = bf_hi(w[e]);
          s1 += lo;
          a += hi;
          s2 = fmaf(lo, lo, s2);
          b = fmaf(hi, hi, b);
        }
        s1 += a;
        s2 += b;
        ++kb;
      };
      unsigned int* fl = &gs_.flag[rb * 32];
#pragma unroll 1
      for (int n = 0; n < 2 * NLAYERS; ++n, fl += 512) {
        const int L = n >> 1;
        (void)L;
        {
          const int lane = tid_now() & 31;
#pragma unroll 1
          while (kb < 8 + (n & 1)) {
            mbar_wait(sb + B_FX + 72 * h + 8 * kb, n & 1);
            tile_stats();
            if (n == 0 && kb == j + 1) copy(h, j);
          }
          s1 = quad_sum(s1) * ((n & 1) ? 1.0f / DM : 1.0f / 512);
          s2 = fmaf(s1 * s1, (n & 1) ? -576.f : -512.f, quad_sum(s2));
          if (n & 1) {
            s2 = inv_sd(s2 * (1.0f / DM));
            s2 *= s2;
          }
          uint4* gs = gs_.stat + rb * 128 + h * 64;
          const uint32_t tag = 4 * ep1 + n;
          if ((lane & 3) == 0) st_tagged(gs + 8 * j + (lane >> 2), __float_as_uint(s1) & ~128u, __float_as_uint(s2) & ~128u, 0u, tag);
          s1 = s2 = 0.f;
          kb = 0;
          TA(14 + (n & 1) * 2);
          uint4 u, v;
#pragma unroll 1
          for (int it = 0; it < SPIN_MAX; ++it) {
            u = ld_tagged(gs + 2 * lane);
            v = ld_tagged(gs + 2 * lane + 1);
            if (__all_sync(0xffffffffu, u.w == tag && v.w == tag)) break;
          }
          if (n == 0) named_bar_sync(6, 96);
          if (n & 1) {
            sts_u32(sb + TAB + h * 512 + lane * 16 + 4, u.y);
            sts_u32(sb + TAB + h * 512 + lane * 16 + 12, v.y);
          } else {
            sts_u4(sb + TAB + h * 512 + lane * 16, u.x, u.y, v.x, v.y);
            fence_proxy_async();
          }
          warp_arrive(sb + B_SR);
          TA(15 + (n & 1) * 2);
        }
        if (!((n & 1) | h)) {
          const int lane = tid_now() & 31;
          const uint32_t dst = sb + (2 - rank) * TILE;
          mbar_wait(sb + B_QK, L);
          TA(18);
          if (rb) {
            auto attempt = [&](uint32_t b) {
              if (elect_one()) {
                mbar_expect_tx(sb + B_HP + 8 * b, 6144);
                bulk_load(dst, gs_.halo + (rb * 8 - 8 + j) * 384, 6144, sb + B_HP + 8 * b);
              }
            };
            attempt(hn & 1);
            __nanosleep(100);
#pragma unroll 1
            for (int it = 0; it < SPIN_MAX; ++it) {
              attempt(~hn & 1);
              mbar_wait(sb + B_HP + 8 * (hn & 1), (hn >> 1) & 1);
              ++hn;
              uint32_t bad = 0;
#pragma unroll
              for (int i = 0; i < 12; ++i) bad |= lds_u32(dst + lane * 16 + 12 + i * 512) ^ (2 * ep1 + L);
              if (__all_sync(0xffffffffu, bad == 0)) break;
            }
          } else {
#pragma unroll 1
            for (int i = 0; i < 12; ++i) sts_u4(dst + lane * 16 + i * 512, 0u, 0u, 0u, 0u);
            __syncwarp();
          }
          if (lane < 2) mbar_arrive(sb + B_NB + 16 * lane);
          TA(19);
          if (rb) {
            mbar_wait(sb + B_HP + 8 * (hn & 1), (hn >> 1) & 1);
            ++hn;
          }
        }
        if (n == 0 && h && (j & 5) == 0) {
          mbar_wait(sb + B_FX + 36 * j + 64, 0);
          copy(j >> 1, 8);
        }
        auto send = [&](int hh, int c) {
          TA(20 + (n & 1) * 20 + c);
          fence_proxy_async();
          if (elect_one()) tma_reduce_3d(&mp.r, sb + hh * HALF + c * TILE, 64 * c, rb * 64 + hh * 32, 0);
          bulk_commit();
        };
        if (!(n & 1)) {
          uint32_t tnext, t;
#pragma unroll 1
          for (int i = 0; i < 5; ++i) {
            const int c = i ? 2 * i - 1 + rank : 0;
            if (i == 1) {
              TA(20 + c);
              named_bar_sync(7 + h, 64);
              if (elect_one()) signal_release(fl + 16 * h + c, 2);
              TA(30 + c);
              continue;
            }
            mbar_wait(sb + B_ST + 72 * h + 8 * i, 0);
            while (true) {
              asm volatile("mov.u32 %0, %%clock;" : "=r"(t));
              if (i == 0 || (int)(t - tnext) >= 0) break;
              __nanosleep(40);
            }
            tnext = i ? tnext + PACE : t + PACE0 + rank * PACE_R;
            if (i == (n ? 4 : 2)) mbar_wait(sb + B_FX + 72 * h, 1);
            if (i == 4) mbar_wait(sb + B_FX + 72 - 72 * h, 1);
            send(h, c);
            bulk_wait<0>();
            if (elect_one()) signal_release(fl + 16 * h + c, i ? 2 : 1);
            TA(30 + c);
          }
        } else {
          if (IMG && n == 1 && NLAYERS > 1 && !h) {
#pragma unroll 1
            for (int s = rb; s < 18; s += 16) {
              const uint32_t bar = sb + B_HP + 8 * (hn & 1), dst = sb + (s >> 4) * HALF + 5 * TILE;
              mbar_wait(sb + B_ST + 72 * (s >> 4), 1);
              load_wq(dst, bar, s);
              mbar_wait(bar, (hn >> 1) & 1);
              ++hn;
              fence_proxy_async();
              __syncwarp();
              if (elect_one()) bulk_store(gs_.wimg + (j * 18 + s) * 1024, dst, SLOT);
            }
          }
#pragma unroll 1
          for (int a = h ^ 1; a < 9; a += 2) {
            mbar_wait(sb + B_ST + 72 + 8 * a, 1);
            send(1, a);
            mbar_wait(sb + B_ST + 8 * a, 1);
            send(0, a);
            if (n < 2 * NLAYERS - 1) {
              bulk_wait<0>();
              if (elect_one()) {
                signal_release(fl + 16 + a);
                signal_relaxed(fl + a);
                if (IMG && a == 1) {
                  signal_relaxed(&gs_.flag[FL_W + j], rb < 2 ? 2 : 1);
                  mbar_arrive(sb + B_S1);
                }
              }
              TA(50 + a);
#pragma unroll 1
              while (kb < min(a - 1, ST_END)) {
                mbar_wait(sb + B_FX + 72 * h + 8 * kb, 0);
                tile_stats();
              }
            }
          }
          bulk_wait<0>();
        }
      }
      }
    }
  } else {
    {
      const int t = threadIdx.x, lane = t & 31;
      uint4 sq[5], so[3];
      if (t < 16 * X_PF) asm volatile("prefetch.global.L2 [%0];" ::"l"(x0 + (size_t)(blockIdx.x * 16 + (t & 15)) * DM + (t >> 4) * 64));
#pragma unroll
      for (int i = 0; i < 5; ++i)
        sq[i] = ldg_u4(wqkv + (size_t)((blockIdx.x & 3) + (t >> 3) * 4 + 128 * i) * NQKV + (blockIdx.x >> 2) * 64 + (t & 7) * 8,
                       blockIdx.x < 108 && (i < 4 || t < 128));
#pragma unroll
      for (int i = 0; i < 3; ++i)
        so[i] = ldg_u4(wo + (size_t)((blockIdx.x - 32) * 6 + warp) * DM + (i * 32 + lane) * 8,
                       blockIdx.x - 32 < 96 && warp < 6 && (i < 2 || lane < 8));
      asm volatile("setmaxnreg.inc.sync.aligned.u32 240;");
      float c[8];
#pragma unroll
      for (int e = 0; e < 8; ++e) c[e] = 0.f;
#pragma unroll
      for (int i = 0; i < 5; ++i) {
        c[0] += bf_lo(sq[i].x); c[1] += bf_hi(sq[i].x); c[2] += bf_lo(sq[i].y); c[3] += bf_hi(sq[i].y);
        c[4] += bf_lo(sq[i].z); c[5] += bf_hi(sq[i].z); c[6] += bf_lo(sq[i].w); c[7] += bf_hi(sq[i].w);
      }
#pragma unroll
      for (int n = 4; n >= 2; n >>= 1) {
        const bool up = lane & (4 * n);
#pragma unroll
        for (int e = 0; e < n; ++e) c[e] = (up ? c[e + n] : c[e]) + __shfl_xor_sync(0xffffffffu, up ? c[e] : c[e + n], 4 * n);
      }
      sts_f2(sb + OVF + warp * 256 + (lane & 7) * 32 + (lane & 24), c[0], c[1]);
      float r = sum8(so[0]) + sum8(so[1]) + sum8(so[2]);
#pragma unroll
      for (int o = 1; o < 32; o <<= 1) r += __shfl_xor_sync(0xffffffffu, r, o);
      if (lane == 0 && blockIdx.x - 32 < 96 && warp < 6) gs_.wsum[(blockIdx.x - 32) * 6 + warp] = r;
      cluster_wait();
      warp_arrive(sb + B_J);
      TA0(13);
    }
    mbar_wait(sb + B_ROLE, 0);
    const bool helper = __shfl_sync(0xffffffffu, lds_u32(sb + S_ROLE), 0) >= 64;
    if (helper) {
      const int wg = warp >> 2;
      const uint32_t da0 = desc_lo_a(sb + wg * HALF), db0 = desc_lo_b(sb + RING, 4096);
      int p = 2;
      uint32_t ph = 0;
      auto mma = [&](float(&d)[64], int kb, bool add) {
        wgmma_fence();
#pragma unroll
        for (int k = 0; k < 4; ++k) wgmma_ss<128>(d, desc_from_lo(da0 + kb * 512 + k * 2), desc_64(db0 + p * 1024 + k * 64), add || k);
        wgmma_commit();
      };
      auto next = [&](bool rel, bool wait, bool more) {
        const int done = p == 0 ? 4 : p - 1;
        if (++p == 5) p = 0;
        if (p == 2) ph ^= 1;
        if (more) mbar_wait(sb + B_FULL + 8 * p, ph);
        if (wait) wgmma_wait<1>();
        release_slot(sb, done, rel);
      };
#pragma unroll 1
      for (uint32_t L = 0; L < NLAYERS; ++L) {
        uint32_t tag;
        uint4* dst;
        auto publish = [&](const uint32_t(&hh)[16], int t, int i) {
          const int b = (i / 3) * 8 + (i % 3) * 3;
          st_tagged(dst + ((t >> 2) * 16 + (t & 3) * 2) * 384 + i * 128, hh[b], hh[b + 1], i % 3 < 2 ? hh[b + 2] : 0u, tag);
        };
        uint32_t h0[16], h1[16], h2[16];
        float prod[32];
        {
          float acc0[64], acc1[64], acc2[64];
#pragma unroll
          for (int i = 0; i < 64; ++i) acc0[i] = acc1[i] = acc2[i] = 0.f;
          mbar_wait(sb + B_FULL + 8 * p, ph);
#pragma unroll 1
          for (int kb = 0; kb < 9; ++kb) {
            mbar_wait(sb + B_FX + 72 * wg + 8 * kb, 0);
            if (kb == 0) TS(9);
            mma(acc0, kb, true);
            next(kb > 0, true, true);
            mma(acc1, kb, true);
            next(true, true, true);
            mma(acc2, kb, true);
            next(true, true, true);
          }
#pragma unroll
          for (int i = 0; i < 16; ++i) {
            h0[i] = pack_bf16(acc0[2 * i] * acc0[32 + 2 * i], acc0[2 * i + 1] * acc0[33 + 2 * i]);
            h1[i] = pack_bf16(acc1[2 * i] * acc1[32 + 2 * i], acc1[2 * i + 1] * acc1[33 + 2 * i]);
          }
          tag = 2 * lds_u32(sb + S_EP) + L;
          dst = gs_.hx + (lds_u32(sb + S_ROLE) * 2 - 128 + rank * 4 + wg) * 8 * 384 + (tid_now() & 127);
          wgmma_wait<0>();
#pragma unroll
          for (int i = 0; i < 32; ++i) prod[i] = acc2[i] * acc2[32 + i];
        }
        TS(10);
        float acc[64];
#pragma unroll 1
        for (int t = 3; t < 8; ++t) {
          mma(acc, 0, false);
#pragma unroll
          for (int i = 0; i < 32; ++i) asm volatile("" : "+f"(prod[i]));
#pragma unroll
          for (int i = 0; i < 16; ++i) h2[i] = pack_bf16(prod[2 * i], prod[2 * i + 1]);
          if (t == 4) {
            stage_done(sb, 8, 1);
            mbar_wait(sb + B_FX + 72 * wg + 8, 1);
          }
          next(true, false, true);
#pragma unroll
          for (int kb = 1; kb < 9; ++kb) {
            mma(acc, kb, true);
            if (kb < 7) {
              publish(h2, t - 1, kb - 1);
              if (t < 5) publish(h0, t - 3, kb - 1);
            }
            if (t == (kb < 8 ? 4 : 3)) mbar_wait(sb + B_FX + 72 * wg + 8 * ((kb + 1) % 9), 1);
            next(true, true, kb < 8 || t < 7);
            if ((t & 3) == 3) stage_done(sb, kb - 1, 1);
          }
#pragma unroll
          for (int i = 0; i < 16; ++i) h0[i] = h1[i];
          wgmma_wait<0>();
#pragma unroll
          for (int i = 0; i < 32; ++i) prod[i] = acc[i] * acc[32 + i];
        }
        TS(11);
#pragma unroll
        for (int i = 0; i < 16; ++i) h2[i] = pack_bf16(prod[2 * i], prod[2 * i + 1]);
#pragma unroll
        for (int i = 0; i < 6; ++i) publish(h2, 7, i);
        release_slot(sb, p == 0 ? 4 : p - 1);
        stage_done(sb, 8, 1);
        TS(12);
      }
    } else
#pragma unroll 1
    for (uint32_t L = 0; L < NLAYERS; ++L) {
      {
        const int wg = warp >> 2;
        float acc[108];
        const uint32_t da0 = desc_lo_a(sb + wg * HALF), db0 = desc_lo_b(sb + RING, 4096);
        int p = 2;
        uint32_t ph = L;
        auto step = [&](int kb, auto U, auto FIRST) {
          constexpr int u = decltype(U)::value, first = decltype(FIRST)::value == 1;
          constexpr bool last = decltype(FIRST)::value == 2;
          wgmma_fence();
#pragma unroll
          for (int k = 0; k < 2; ++k)
            wgmma_ss<216>(acc, desc_from_lo(da0 + kb * 512 + u * 4 + k * 2), desc_from_lo(db0 + p * 1024 + k * 128), !first || u || k);
          wgmma_commit();
          if (last && wg) asm volatile("bar.arrive 5, 256;" ::: "memory");
          const int prev = p == 0 ? 4 : p - 1;
          if (++p == 5) p = 0;
          if (p == 2) ph ^= 1;
          if (!last) {
            if (u) mbar_wait2(sb + B_FX + 72 * wg + 8 * kb + 8, 0, sb + B_FULL + 8 * p, ph);
            else mbar_wait(sb + B_FULL + 8 * p, ph);
          }
          if (!first || u) {
            wgmma_wait<1>();
            release_slot(sb, prev);
          }
        };
        mbar_wait2(sb + B_FX + 72 * wg, 0, sb + B_FULL + 8 * p, ph);
        TR(1);
        step(0, IC<0>{}, IC<1>{});
        step(0, IC<1>{}, IC<1>{});
        float s1[2] = {0.f, 0.f}, s2[2] = {0.f, 0.f};
        bool todo = true;
        const int stop = wg ? 8 : Q_H;
        auto last_tile = [&]() {
          const int lane = tid_now() & 31;
#pragma unroll
          for (int r = 0; r < 2; ++r) {
            const uint32_t ad = sb + wg * HALF + 8 * TILE + (warp & 3) * 2048 + r * 1024 + (lane & 28) * 32 + (lane & 7) * 16;
            const uint4 u = lds_u4(ad), v = lds_u4(ad ^ 64);
            const uint32_t w[8] = {u.x, u.y, u.z, u.w, v.x, v.y, v.z, v.w};
            float a = 0.f, b = 0.f, c = 0.f, d = 0.f;
#pragma unroll
            for (int e = 0; e < 8; ++e) {
              const float lo = bf_lo(w[e]), hi = bf_hi(w[e]);
              a += lo;
              b += hi;
              c = fmaf(lo, lo, c);
              d = fmaf(hi, hi, d);
            }
            s1[r] = quad_sum(a + b) * (1.0f / 64);
            s2[r] = fmaf(s1[r] * s1[r], -64.f, quad_sum(c + d));
          }
          todo = false;
        };
#pragma unroll 1
        for (int kb = 1; kb < 9; ++kb) {
          TR(1 + kb);
          if (Q_H < 8 && kb == stop) mbar_wait(sb + B_FX + 72 * wg + 64, 0);
          if (todo && kb >= (wg ? Q_ST1 : Q_ST0) && __all_sync(0xffffffffu, mbar_test(sb + B_FX + 72 * wg + 64, 0))) last_tile();
          if (kb == stop) break;
          step(kb, IC<0>{}, IC<0>{});
          step(kb, IC<1>{}, IC<0>{});
        }
        const int tid = tid_now(), lane = tid & 31, g = lane >> 2, q = lane & 3;
        if (lane == 0 && wg == 0) mbar_arrive(sb + B_QK);
        mbar_wait2(sb + B_SR, 0, sb + B_AUX, L);
        float2 st0 = lds_f2(sb + TAB + (warp * 16 + g) * 8), st1 = lds_f2(sb + TAB + (warp * 16 + g) * 8 + 64);
        s1[0] -= st0.x;
        s1[1] -= st1.x;
        st0.x = fmaf(s1[0], 1.0f / 9, st0.x);
        st1.x = fmaf(s1[1], 1.0f / 9, st1.x);
        st0.y = fmaf(s1[0] * s1[0], 512.f / 9, st0.y + s2[0]);
        st1.y = fmaf(s1[1] * s1[1], 512.f / 9, st1.y + s2[1]);
        if (wg == 0) named_bar_sync(5, 256);
        wgmma_fence();
        wgmma_rs<216>(acc, q ? 0u : pack_bf16(-st0.x, -st0.x), q ? 0u : pack_bf16(-st1.x, -st1.x), 0u, 0u, desc_sbo(desc_lo_b(sb + OVF, 256), 0), 1);
        wgmma_commit();
        if (Q_H < 8) {
#pragma unroll 1
          for (int kb = stop; kb < 8; ++kb) {
            step(kb, IC<0>{}, IC<0>{});
            step(kb, IC<1>{}, IC<0>{});
          }
        }
        step(8, IC<0>{}, IC<0>{});
        step(8, IC<1>{}, IC<2>{});
        TR(10);
        st0.y = inv_sd(st0.y * (1.0f / DM));
        st1.y = inv_sd(st1.y * (1.0f / DM));
        const uint32_t ep1 = lds_u32(sb + S_EP), role = lds_u32(sb + S_ROLE);
        const bool first = (warp & 5) == 0 && role < 4;
        const bool e0 = 2 * q > g, e1 = 2 * q + 1 > g;
        float fs[2][2], fp[2][2], fb[2];
        {
          const float k0 = __shfl_sync(0xffffffffu, st0.y, 8 * q), k1 = __shfl_sync(0xffffffffu, st0.y, 8 * q + 4);
          const float c = 0.23570226039551584f * 1.4426950408889634f;
          fp[0][0] = e0 ? 1.f : k0;
          fp[0][1] = e1 ? 1.f : k1;
          fp[1][0] = e0 ? k0 : 1.f;
          fp[1][1] = e1 ? k1 : 1.f;
#pragma unroll
          for (int i = 0; i < 4; ++i) fs[i >> 1][i & 1] = fp[i >> 1][i & 1] * ((i >> 1) ? st1.y : st0.y) * c;
          fb[0] = first && e0 ? -INFINITY : 0.f;
          fb[1] = first && e1 ? -INFINITY : 0.f;
        }
        const int sw = (warp & 1) ? warp + 3 : warp + 1;
        const uint64_t nbp = sw >= 8 ? (uint64_t)(gs_.halo + (role * 2 + rank) * 384 + (warp & 2) * 96 + lane)
                                     : (uint64_t)(smem + (sw >> 2) * HALF + (2 + 2 * (sw & 1) - rank) * TILE + (sw & 2) * 1536 + lane * 16);
        const uint32_t nbb = lane ? mapa(sb + B_RX + 8 * wg, rank ^ 1) : mapa(sb + B_NB + 8 * (sw & 7), rank);
        const bool nba = lane ? lane == 1 : sw < 8;
        if (tid == 128 * wg) mbar_expect_tx(sb + B_OX + 8 * wg, 10240);
        __syncwarp();
        wgmma_wait<0>();
        release_slot(sb, 4);
        TS(1);
        uint32_t Q[2][9], K[3][9], V[3][9];
        auto pack = [&](auto R) {
          constexpr int r = decltype(R)::value;
#pragma unroll
          for (int i = 0; i < 9; ++i) {
            const int c = (i + 9 - r) % 9, jv = c < 8 ? 64 + 4 * c : 104;
            V[2][i] = movm(pack_bf16(acc[jv + 2] * st1.y, acc[jv + 3] * st1.y));
          }
#pragma unroll
          for (int i = 0; i < 9; ++i) {
            const int c = (i + 9 - r) % 9, jk = c < 8 ? 32 + 4 * c : 100;
            K[2][i] = pack_bf16(acc[jk + 2] * st1.y, acc[jk + 3] * st1.y);
          }
#pragma unroll
          for (int i = 0; i < 6; ++i) {
            const uint32_t(&d)[9] = i < 3 ? K[2] : V[2];
            st_tagged_any(nbp + i * 512, d[3 * (i % 3)], d[3 * (i % 3) + 1], d[3 * (i % 3) + 2], 2 * ep1 + L);
          }
          __syncwarp();
          mbar_arrive_if(nbb, nba);
#pragma unroll
          for (int i = 0; i < 9; ++i) {
            const int c = (i + 9 - r) % 9, jq = c < 8 ? 4 * c : 96, jk = c < 8 ? 32 + 4 * c : 100, jv = c < 8 ? 64 + 4 * c : 104;
            V[1][i] = movm(pack_bf16(acc[jv], acc[jv + 1]));
            Q[0][i] = pack_bf16(acc[jq], acc[jq + 1]);
            Q[1][i] = pack_bf16(acc[jq + 2], acc[jq + 3]);
            K[1][i] = pack_bf16(acc[jk], acc[jk + 1]);
          }
        };
        if (rank) pack(IC<1>{});
        else pack(IC<0>{});
        uint32_t qf[4][2], ql[4][2];
        float sc[4][3][4];
        auto logits = [&](int t) {
#pragma unroll
          for (int h = 0; h < 4; ++h) {
            mma_1688(sc[h][t], ql[h][0], ql[h][1], K[t][2 * h + 2]);
            mma_16816(sc[h][t], qf[h][0], qf[h][1], Q[0][2 * h + 1], Q[1][2 * h + 1], K[t][2 * h], K[t][2 * h + 1]);
          }
        };
#pragma unroll
        for (int i = 0; i < 8; ++i) {
          qf[i >> 1][i & 1] = q >= (i >> 1) ? Q[i & 1][i & 6] : 0u;
          ql[i >> 1][i & 1] = q <= (i >> 1) ? Q[i & 1][(i & 6) + 2] : 0u;
        }
        logits(1);
        logits(2);
        float2 ws[9];
#pragma unroll
        for (int i = 0; i < 9; ++i) ws[i] = lds_f2(sb + S_WS + i * 32 + 8 * q);
        uint32_t of[9][2];
        float o0[9][2];
        auto rows = [&](auto R, float(&o)[9][2]) {
          constexpr int r = decltype(R)::value;
          float pr[4][2], mx[4];
#pragma unroll
          for (int h = 0; h < 4; ++h) {
            pr[h][0] = fmaf(e0 ? sc[h][r][2 * r] : sc[h][r + 1][2 * r], fs[r][0], r ? 0.f : fb[0]);
            pr[h][1] = fmaf(e1 ? sc[h][r][2 * r + 1] : sc[h][r + 1][2 * r + 1], fs[r][1], r ? 0.f : fb[1]);
            mx[h] = fmaxf(pr[h][0], pr[h][1]);
          }
#pragma unroll
          for (int i = 0; i < 8; ++i) mx[i & 3] = fmaxf(mx[i & 3], __shfl_xor_sync(0xffffffffu, mx[i & 3], 1 + (i >> 2)));
#pragma unroll
          for (int h = 0; h < 4; ++h) {
#pragma unroll
            for (int e = 0; e < 2; ++e) asm("ex2.approx.ftz.f32 %0, %1;" : "=f"(pr[h][e]) : "f"(pr[h][e] - mx[h]));
            mx[h] = pr[h][0] + pr[h][1];
            pr[h][0] *= fp[r][0];
            pr[h][1] *= fp[r][1];
          }
#pragma unroll
          for (int i = 0; i < 8; ++i) mx[i & 3] += __shfl_xor_sync(0xffffffffu, mx[i & 3], 1 + (i >> 2));
          const uint32_t me = (e0 ? 0xFFFFu : 0u) | (e1 ? 0xFFFF0000u : 0u);
          uint32_t pp[4];
#pragma unroll
          for (int h = 0; h < 4; ++h) {
            pp[h] = pack_bf16(pr[h][0], pr[h][1]);
            asm("rcp.approx.ftz.f32 %0, %1;" : "=f"(mx[h]) : "f"(mx[h]));
          }
#pragma unroll
          for (int i = 0; i < 9; ++i) {
            const int h = i < 4 ? 0 : i < 5 ? 1 : 2;
            float d[4];
            mma_16816_z(d, pp[h] & me, pp[h + 1] & me, pp[h] & ~me, pp[h + 1] & ~me, V[r][i], V[r + 1][i]);
            const bool up = i == 2 * h + 2 ? q > h : i > 2 * h + 2;
            const float inv = up ? mx[h + 1] : mx[h];
            o[i][0] = (up ? d[2] : d[0]) * inv;
            o[i][1] = (up ? d[3] : d[1]) * inv;
            of[i][r] = pack_bf16(o[i][0], o[i][1]);
          }
        };
        auto shift = [&](const float(&o)[9][2]) {
          float a = 0.f, b = 0.f, c = 0.f;
#pragma unroll
          for (int i = 0; i < 3; ++i) {
            a = fmaf(o[i][0], ws[i].x, fmaf(o[i][1], ws[i].y, a));
            b = fmaf(o[i + 3][0], ws[i + 3].x, fmaf(o[i + 3][1], ws[i + 3].y, b));
            c = fmaf(o[i + 6][0], ws[i + 6].x, fmaf(o[i + 6][1], ws[i + 6].y, c));
          }
          return a + b + c;
        };
        rows(IC<1>{}, o0);
        float sh1 = shift(o0);
        mbar_wait3(sb + B_FULL, L ^ 1, sb + B_RX + 8 * wg, L, sb + B_NB + 8 * warp, L);
#pragma unroll
        for (int i = 0; i < 6; ++i) {
          const uint4 u = lds_u4(sb + wg * HALF + (2 + 2 * (warp & 1) - rank) * TILE + (warp & 2) * 1536 + lane * 16 + i * 512);
          uint32_t(&d)[9] = i < 3 ? K[0] : V[0];
          d[3 * (i % 3)] = u.x;
          d[3 * (i % 3) + 1] = u.y;
          d[3 * (i % 3) + 2] = u.z;
        }
        TS(3);
        logits(0);
        rows(IC<0>{}, o0);
        TS(5);
        float wa[3][32];
        const uint32_t dw0 = desc_lo_b(sb + RING, 0);
        wgmma_fence();
#pragma unroll
        for (int k = 0; k < 5; ++k)
          wgmma_rs<64>(wa[0], of[2 * k][0], of[2 * k][1], k < 4 ? of[2 * k + 1][0] : 0u, k < 4 ? of[2 * k + 1][1] : 0u,
                       desc_sbo(dw0 + k * 128, k < 4 ? 1024 : 0), k);
        wgmma_commit();
        const uint32_t xa = sb + wg * HALF + 3 * TILE + (warp & 3) * 2048 + lane * 16;
        const uint32_t xr = mapa(xa + (rank ^ 1) * TILE, rank ^ 1), xb = mapa(sb + B_OX + 8 * wg, rank ^ 1);
#pragma unroll
        for (int i = 0; i < 4; ++i) st_async_u4(xr + i * 512, xb, of[2 * i][0], of[2 * i][1], of[2 * i + 1][0], of[2 * i + 1][1]);
        float sh0 = fmaf(quad_sum(shift(o0)), 1.0f / DM, st0.x * 0.125f);
        sh1 = fmaf(quad_sum(sh1), 1.0f / DM, st1.x * 0.125f);
        st_async_u4(xr + 2 * TILE, xb, of[8][0], of[8][1], __float_as_uint(sh0), __float_as_uint(sh1));
        wgmma_wait<0>();
        stage_tile(wa[0], 1.f, -sh0, 1.f, -sh1, sb, 0, 0, 1);
        TS(6);
        uint4 xv[5];
        auto issue = [&](auto I, auto PART) {
          constexpr int i = decltype(I)::value, part = decltype(PART)::value;
          const uint32_t lo = dw0 + (2 * i - 1) * (WOA / 16);
          if (part & 1) mbar_wait(sb + B_FULL + 8 * i, (i == 1) ^ L);
          wgmma_fence();
          if (part & 1) {
#pragma unroll
            for (int k = 0; k < 4; ++k)
              wgmma_rs<64>(wa[i % 3], of[2 * k][0], of[2 * k][1], of[2 * k + 1][0], of[2 * k + 1][1], desc_sbo(lo + k * 128, 1024), k);
          }
          if (part & 2) {
            wgmma_rs<64>(wa[i % 3], of[8][0], of[8][1], xv[4].x, xv[4].y, desc_sbo(lo + 512, WOA), 1);
#pragma unroll
            for (int k = 0; k < 4; ++k)
              wgmma_rs<64>(wa[i % 3], xv[k].x, xv[k].y, xv[k].z, xv[k].w, desc_sbo(lo + WOA / 16 + k * 128, 1024), 1);
          }
          wgmma_commit();
        };
        issue(IC<1>{}, IC<1>{});
        if (q < 2) sts_u32(sb + TAB + (warp * 16 + g + 8 * q) * 8, __float_as_uint(q ? sh1 : sh0));
        mbar_wait(sb + B_OX + 8 * wg, L);
#pragma unroll
        for (int i = 0; i < 5; ++i) xv[i] = lds_u4(xa + rank * TILE + (i < 4 ? i * 512 : 2 * TILE));
        sh0 += __uint_as_float(xv[4].z);
        sh1 += __uint_as_float(xv[4].w);
        TS(4);
        issue(IC<1>{}, IC<2>{});
        wgmma_wait<0>();
        release_slot(sb, 0);
        stage_tile(wa[1], 1.f, -sh0, 1.f, -sh1, sb, 1 + rank, 1, 1);
        mbar_wait(sb + B_ST, 0);
        issue(IC<2>{}, IC<3>{});
        issue(IC<3>{}, IC<3>{});
        wgmma_wait<1>();
        release_slot(sb, 1);
        issue(IC<4>{}, IC<3>{});
        stage_tile(wa[2], 1.f, -sh0, 1.f, -sh1, sb, 3 + rank, 0, 0);
        wgmma_wait<1>();
        release_slot(sb, 2);
        stage_tile(wa[0], 1.f, -sh0, 1.f, -sh1, sb, 5 + rank, 0, 0);
        wgmma_wait<0>();
        release_slot(sb, 3);
        release_slot(sb, 4);
        stage_tile(wa[1], 1.f, -sh0, 1.f, -sh1, sb, 7 + rank, 2, 7);
        TS(7);
      }
      uint32_t hreg[9][16];
      {
        const int wg = warp >> 2;
        float acc[64];
        int p = 0;
        uint32_t ph = L;
        const uint32_t da0 = desc_lo_a(sb + wg * HALF), db0 = desc_lo_b(sb + RING, 8192);
        float prod[32];
        {
          float acc0[64], acc1[64], acc2[64];
#pragma unroll
          for (int i = 0; i < 64; ++i) acc0[i] = acc1[i] = acc2[i] = 0.f;
          auto step = [&](float(&d)[64], int kb, bool rel) {
            mbar_wait(sb + B_FULL + 8 * p, ph);
            wgmma_fence();
#pragma unroll
            for (int k = 0; k < 4; ++k)
              wgmma_ss<128>(d, desc_from_lo(da0 + kb * 512 + k * 2), desc_from_lo(db0 + p * 1024 + k * 128), 1);
            wgmma_commit();
            wgmma_wait<1>();
            release_slot(sb, p == 0 ? 4 : p - 1, rel);
            if (++p == 5) p = 0;
            if (p == 2) ph ^= 1;
          };
#pragma unroll 1
          for (int kb = 0; kb < 9; ++kb) {
            mbar_wait(sb + B_FX + 72 * wg + 8 * kb, 1);
            if (kb == 0) TS(9);
            TR(16 + kb);
            step(acc0, kb, kb > 0);
            step(acc1, kb, true);
            step(acc2, kb, true);
          }
#pragma unroll
          for (int i = 0; i < 16; ++i) {
            hreg[0][i] = pack_bf16(acc0[2 * i] * acc0[32 + 2 * i], acc0[2 * i + 1] * acc0[33 + 2 * i]);
            hreg[1][i] = pack_bf16(acc1[2 * i] * acc1[32 + 2 * i], acc1[2 * i + 1] * acc1[33 + 2 * i]);
          }
          mbar_wait(sb + B_FULL + 8 * p, ph);
          wgmma_wait<0>();
#pragma unroll
          for (int i = 0; i < 32; ++i) prod[i] = acc2[i] * acc2[32 + i];
        }
#pragma unroll
        for (int t = 2; t < 7; ++t)
#pragma unroll
          for (int i = 0; i < 16; ++i) hreg[t][i] = 0u;
        TS(10);
#pragma unroll 1
        for (int t = 3; t < 8; ++t) {
          wgmma_fence();
#pragma unroll
          for (int k = 0; k < 4; ++k)
            wgmma_ss<128>(acc, desc_from_lo(da0 + k * 2), desc_from_lo(db0 + p * 1024 + k * 128), k != 0);
          wgmma_commit();
          release_slot(sb, p == 0 ? 4 : p - 1);
#pragma unroll
          for (int i = 0; i < 32; ++i) asm volatile("" : "+f"(prod[i]));
#pragma unroll
          for (int i = 0; i < 16; ++i) hreg[8][i] = pack_bf16(prod[2 * i], prod[2 * i + 1]);
          if (++p == 5) p = 0;
          if (p == 2) ph ^= 1;
          mbar_wait(sb + B_FULL + 8 * p, ph);
#pragma unroll 1
          for (int kb = 1; kb < 9; ++kb) {
            wgmma_fence();
#pragma unroll
            for (int k = 0; k < 4; ++k)
              wgmma_ss<128>(acc, desc_from_lo(da0 + kb * 512 + k * 2), desc_from_lo(db0 + p * 1024 + k * 128), 1);
            wgmma_commit();
            if (kb == 1) {
#pragma unroll
              for (int tt = 2; tt < 7; ++tt)
                if (t == tt + 1) {
#pragma unroll
                  for (int i = 0; i < 16; ++i) asm volatile("mov.b32 %0, %1;" : "=r"(hreg[tt][i]) : "r"(hreg[8][i]));
                }
            }
            const int done = p == 0 ? 4 : p - 1;
            if (++p == 5) p = 0;
            if (p == 2) ph ^= 1;
            if (GU_PRE) mbar_wait(sb + B_FULL + 8 * p, ph);
            wgmma_wait<1>();
            release_slot(sb, done);
            if (!GU_PRE) mbar_wait(sb + B_FULL + 8 * p, ph);
          }
          wgmma_wait<0>();
#pragma unroll
          for (int i = 0; i < 32; ++i) prod[i] = acc[i] * acc[32 + i];
          TR(32 + t);
        }
        auto tail = [&](auto NN) {
          constexpr int N = decltype(NN)::value;
          float acc[N / 2];
          const uint32_t db = desc_lo_b(sb + RING, N == 64 ? 8192 : 4096);
          auto mma = [&](int kb, bool first) {
            wgmma_fence();
#pragma unroll
            for (int k = 0; k < 4; ++k)
              wgmma_ss<N>(acc, desc_from_lo(da0 + kb * 512 + k * 2), desc_64(db + p * 1024 + k * 64), !first || k);
            wgmma_commit();
          };
          mma(0, true);
          release_slot(sb, p == 0 ? 4 : p - 1);
#pragma unroll
          for (int i = 0; i < 32; ++i) asm volatile("" : "+f"(prod[i]));
#pragma unroll
          for (int i = 0; i < 16; ++i) hreg[7][i] = pack_bf16(prod[2 * i], prod[2 * i + 1]);
          if (++p == 5) p = 0;
          if (p == 2) ph ^= 1;
          mbar_wait(sb + B_FULL + 8 * p, ph);
          uint4 hx[3] = {};
          const uint4* src = gs_.hx;
          uint32_t tag = 0;
          if (N == 64) {
            src += (lds_u32(sb + S_ROLE) * 2 + rank) * 384 + (tid_now() & 127);
            tag = 2 * lds_u32(sb + S_EP) + L;
          }
          auto fetch = [&]() {
#pragma unroll
            for (int i = 0; i < 3; ++i) hx[i] = ld_tagged(src + i * 128);
          };
#pragma unroll 1
          for (int kb = 1; kb < 9; ++kb) {
            if (N == 128 && kb == T_HOLD) named_bar_sync(5, 256);
            mma(kb, false);
            if (N == 64 && kb == T_LEAD) asm volatile("bar.arrive 5, 256;" ::: "memory");
            if (N == 64 && kb == KH) fetch();
            const int done = p == 0 ? 4 : p - 1;
            if (++p == 5) p = 0;
            if (p == 2) ph ^= 1;
            mbar_wait(sb + B_FULL + 8 * p, ph);
            wgmma_wait<1>();
            release_slot(sb, done);
          }
          if (N == 64) {
#pragma unroll 1
            for (int it = 0; it < SPIN_MAX; ++it) {
              if (__all_sync(0xffffffffu, hx[0].w == tag && hx[1].w == tag && (hx[2].w | hx[2].z) == tag)) break;
              fetch();
            }
            const uint32_t w[8] = {hx[0].x, hx[0].y, hx[0].z, hx[1].x, hx[1].y, hx[1].z, hx[2].x, hx[2].y};
#pragma unroll
            for (int i = 0; i < 8; ++i) hreg[8][8 + i] = w[i] ^ hx[i / 3].w ^ tag;
#pragma unroll
            for (int i = 8; i < 16; ++i) asm volatile("" : "+r"(hreg[8][i]));
          }
          wgmma_wait<0>();
#pragma unroll
          for (int i = 0; i < N / 8; ++i) hreg[8][i] = pack_bf16(acc[2 * i] * acc[N / 4 + 2 * i], acc[2 * i + 1] * acc[N / 4 + 2 * i + 1]);
        };
        if (wg) tail(IC<64>{});
        else tail(IC<128>{});
      }
      TS(11);
      {
        float accA[32], accB[32];
#pragma unroll
        for (int i = 16; i < 32; ++i) accB[i] = 0.f;
        int p = 1;
        uint32_t ph = L;
        const uint32_t db0 = desc_lo_b(sb + RING, 8192);
        int prev = 0, left = 35;
        auto stage = [&](auto S, auto NU, bool rel) {
          constexpr int s = decltype(S)::value;
          const uint32_t dlo = p < 5 ? db0 + p * 1024 : db0 - RING / 16 + 1024 + p * 512, dv = p < 5 ? 512 : HALF / 16;
          wgmma_fence();
#pragma unroll
          for (int v = 0; v < decltype(NU)::value; ++v) {
            const int u = 2 * s + v, kq = u % 9;
#pragma unroll
            for (int k = 0; k < 4; ++k)
              wgmma_rs<64>(u >= 9 ? accB : accA, hreg[kq][4 * k], hreg[kq][4 * k + 1], hreg[kq][4 * k + 2], hreg[kq][4 * k + 3],
                           desc_from_lo(dlo + v * dv + k * 128), (kq | k) != 0);
          }
          wgmma_commit();
          const int done = prev;
          prev = p;
          --left;
          if (++p == (left > 0 ? 7 : 5)) p = 0;
          if (p == 2) ph ^= 1;
          if (decltype(NU)::value == 2) mbar_wait(sb + B_FULL + 8 * p, ph ^ (p >= 5));
          if (rel) {
            wgmma_wait<1>();
            release_slot(sb, done, done < 5 || left > 1);
          }
        };
        stage(IC<0>{}, IC<2>{}, false);
        release_slot(sb, 0);
        mbar_wait(sb + B_SR, 1);
        release_slot(sb, 5);
        release_slot(sb, 6);
        const uint32_t ta = sb + TAB + warp * 128 + (tid_now() & 28) * 2;
        const float2 t0 = lds_f2(ta), t1 = lds_f2(ta + 64);
        const float m0 = t0.y, c0 = t0.x, m1 = t1.y, c1 = t1.x;
#pragma unroll 1
        for (int i = 0; i < 4; ++i) {
          stage(IC<1>{}, IC<2>{}, true);
          if (i) stage_tile<2, 4>(accB, m0, c0, m1, c1, sb, 2 * i - 1, 0, 0);
          stage(IC<2>{}, IC<2>{}, true);
          if (i) stage_done(sb, 2 * i - 1, 1);
          stage(IC<3>{}, IC<2>{}, true);
          stage(IC<4>{}, IC<2>{}, true);
          stage(IC<5>{}, IC<2>{}, true);
          stage_tile<0, 2>(accA, m0, c0, m1, c1, sb, 2 * i, 0, 0);
          TR(48 + 2 * i);
          stage(IC<6>{}, IC<2>{}, true);
          stage_tile<2, 4>(accA, m0, c0, m1, c1, sb, 2 * i, 0, 0);
          stage(IC<7>{}, IC<2>{}, true);
          stage_done(sb, 2 * i, 1);
          if (i == 3 && (tid_now() & 31) == 0) mbar_arrive(sb + B_XF);
          stage(IC<8>{}, IC<2>{}, true);
          stage(IC<0>{}, IC<2>{}, true);
          if (IMG && i == 2 && L + 1 < NLAYERS) mbar_wait(sb + B_S1, 0);
          if (i == 3) mbar_wait(sb + B_XF, L);
          stage_tile<0, 2>(accB, m0, c0, m1, c1, sb, 2 * i + 1, 0, 0);
          TR(49 + 2 * i);
        }
        stage(IC<1>{}, IC<2>{}, true);
        stage_tile<2, 4>(accB, m0, c0, m1, c1, sb, 7, 7, DN_LATE ? 0 : 1);
        stage(IC<2>{}, IC<2>{}, true);
        if (DN_LATE) stage_done(sb, 7, 1);
        stage(IC<3>{}, IC<2>{}, true);
        stage(IC<4>{}, IC<1>{}, true);
        wgmma_wait<0>();
        release_slot(sb, 1);
        stage_tile(accA, m0, c0, m1, c1, sb, 8, 8, 1);
        TR(56);
        TS(12);
      }
    }
  }
}

__global__ void probe_kernel() {}

typedef CUresult (*PFN_tmEncode)(CUtensorMap*, CUtensorMapDataType, cuuint32_t, void*, const cuuint64_t*,
                                 const cuuint64_t*, const cuuint32_t*, const cuuint32_t*, CUtensorMapInterleave,
                                 CUtensorMapSwizzle, CUtensorMapL2promotion, CUtensorMapFloatOOBfill);

static void encode_2d(PFN_tmEncode fn, CUtensorMap* m, const void* ptr, uint64_t inner, uint64_t outer, uint32_t box_inner,
                      uint32_t box_outer) {
  cuuint64_t dims[2] = {inner, outer};
  cuuint64_t strides[1] = {inner * 2};
  cuuint32_t box[2] = {box_inner, box_outer};
  cuuint32_t estr[2] = {1, 1};
  fn(m, CU_TENSOR_MAP_DATA_TYPE_BFLOAT16, 2, const_cast<void*>(ptr), dims, strides, box, estr,
     CU_TENSOR_MAP_INTERLEAVE_NONE, box_inner < 64 ? CU_TENSOR_MAP_SWIZZLE_64B : CU_TENSOR_MAP_SWIZZLE_128B,
     box_inner < 64 ? CU_TENSOR_MAP_L2_PROMOTION_L2_128B : CU_TENSOR_MAP_L2_PROMOTION_L2_256B, CU_TENSOR_MAP_FLOAT_OOB_FILL_NONE);
}

static void encode_3d(PFN_tmEncode fn, CUtensorMap* m, const void* ptr, uint64_t d0, uint64_t d1, uint64_t d2, uint64_t s1,
                      uint64_t s2, uint32_t b0, uint32_t b1, uint32_t b2, CUtensorMapL2promotion prom) {
  cuuint64_t dims[3] = {d0, d1, d2};
  cuuint64_t strides[2] = {s1, s2};
  cuuint32_t box[3] = {b0, b1, b2};
  cuuint32_t estr[3] = {1, 1, 1};
  fn(m, CU_TENSOR_MAP_DATA_TYPE_BFLOAT16, 3, const_cast<void*>(ptr), dims, strides, box, estr, CU_TENSOR_MAP_INTERLEAVE_NONE,
     b0 < 64 ? CU_TENSOR_MAP_SWIZZLE_64B : CU_TENSOR_MAP_SWIZZLE_128B, prom, CU_TENSOR_MAP_FLOAT_OOB_FILL_NONE);
}

}

extern "C" void kernel_launch(void* const* d_in, const int* in_sizes, int n_in, void* d_out, int out_size) {
  const __nv_bfloat16* x0 = (const __nv_bfloat16*)d_in[0];
  const __nv_bfloat16* wqkv = (const __nv_bfloat16*)d_in[1];
  const __nv_bfloat16* wo = (const __nv_bfloat16*)d_in[2];
  const __nv_bfloat16* wg = (const __nv_bfloat16*)d_in[4];
  const __nv_bfloat16* wu = (const __nv_bfloat16*)d_in[5];
  const __nv_bfloat16* wd = (const __nv_bfloat16*)d_in[6];
  static PFN_tmEncode enc = nullptr;
  if (!enc) {
    void* fn = nullptr;
    cudaDriverEntryPointQueryResult qr;
    cudaGetDriverEntryPoint("cuTensorMapEncodeTiled", &fn, cudaEnableDefault, &qr);
    enc = (PFN_tmEncode)fn;
  }
  Maps mp;
  encode_3d(enc, &mp.x0, x0, DM, SEQ / 2, 2, DM * 4, DM * 2, 64, 32, 2, CU_TENSOR_MAP_L2_PROMOTION_L2_256B);
  encode_3d(enc, &mp.r, d_out, DM, SEQ / 2, 2, DM * 4, DM * 2, 64, 32, 2, CU_TENSOR_MAP_L2_PROMOTION_L2_256B);
  encode_3d(enc, &mp.wq, wqkv, 576, 576, 3, NQKV * 2, 576 * 2, 64, 32, 3, CU_TENSOR_MAP_L2_PROMOTION_L2_128B);
  encode_2d(enc, &mp.wo, wo, DM, DM, 64, 72);
  encode_2d(enc, &mp.wg, wg, FF, DM, 64, 64);
  encode_2d(enc, &mp.wu, wu, FF, DM, 64, 64);
  encode_2d(enc, &mp.wd, wd, DM, FF, 64, 64);
  encode_3d(enc, &mp.tg, wg, 32, DM, FF / 32, FF * 2, 64, 32, 64, 2, CU_TENSOR_MAP_L2_PROMOTION_L2_128B);
  encode_3d(enc, &mp.tu, wu, 32, DM, FF / 32, FF * 2, 64, 32, 64, 2, CU_TENSOR_MAP_L2_PROMOTION_L2_128B);
  encode_2d(enc, &mp.hg, wg, FF, DM, 32, 64);
  encode_2d(enc, &mp.hu, wu, FF, DM, 32, 64);
  cudaFuncSetAttribute(mega_kernel, cudaFuncAttributeMaxDynamicSharedMemorySize, SMEM_BYTES);
  static int small_gpc = -1;
  if (small_gpc < 0) {
    cudaFuncSetAttribute(probe_kernel, cudaFuncAttributeMaxDynamicSharedMemorySize, SMEM_BYTES);
    cudaFuncSetAttribute(probe_kernel, cudaFuncAttributeNonPortableClusterSizeAllowed, 1);
    int n[2] = {0, 0};
    for (int i = 0; i < 2; ++i) {
      cudaLaunchConfig_t cfg = {};
      cfg.gridDim = dim3(128);
      cfg.blockDim = dim3(384);
      cfg.dynamicSmemBytes = SMEM_BYTES;
      cudaLaunchAttribute at;
      at.id = cudaLaunchAttributeClusterDimension;
      at.val.clusterDim.x = 8 << i;
      at.val.clusterDim.y = at.val.clusterDim.z = 1;
      cfg.attrs = &at;
      cfg.numAttrs = 1;
      if (cudaOccupancyMaxActiveClusters(&n[i], probe_kernel, &cfg) != cudaSuccess) cudaGetLastError();
    }
    small_gpc = n[0] == 15 && n[1] == 7;
  }
  mega_kernel<<<NCTA, 384, SMEM_BYTES, cudaStreamPerThread>>>(mp, x0, wqkv, wo, (__nv_bfloat16*)d_out, small_gpc);
}
```

```cpp
#include <cuda_runtime.h>
#include <cuda_bf16.h>
#include <cuda.h>
#include <stdint.h>

namespace {

constexpr int SEQ = 2048, DM = 576, FF = 4608, NQKV = 1728, NCTA = 132;

constexpr int FL_J = 64 * 32, FL_W = FL_J + 32;
struct Scratch {
  unsigned int flag[FL_W + 32];
  unsigned int epoch[160];
  unsigned int claim[32];
  float wsum[DM];
  float csq[4 * NQKV];
  uint4 stat[SEQ];
  uint4 halo[128 * 384];
  uint4 hx[128 * 384];
  uint4 himg[36 * 1024];
  uint4 wimg[8 * 18 * 1024];
};
__device__ __align__(1024) Scratch gs_;

__device__ __forceinline__ uint32_t smem_u32(const void* p) { return (uint32_t)__cvta_generic_to_shared(p); }
__device__ __forceinline__ void mbar_init(uint32_t bar, uint32_t count) {
  asm volatile("mbarrier.init.shared::cta.b64 [%0], %1;" ::"r"(bar), "r"(count) : "memory");
}
__device__ __forceinline__ void mbar_expect_tx(uint32_t bar, uint32_t bytes) {
  asm volatile("mbarrier.arrive.expect_tx.shared::cta.b64 _, [%0], %1;" ::"r"(bar), "r"(bytes) : "memory");
}
__device__ __forceinline__ void mbar_arrive(uint32_t bar) {
  asm volatile("mbarrier.arrive.shared::cta.b64 _, [%0];" ::"r"(bar) : "memory");
}
#define SPIN_LIMIT "1048576"
#define SPIN_MAX 1048576
__device__ __forceinline__ void mbar_wait(uint32_t bar, uint32_t parity) {
  asm volatile(
      "{\n.reg .pred p, c;\n.reg .u32 n;\nmov.u32 n, 0;\n"
      "WAIT:\nmbarrier.try_wait.parity.shared::cta.b64 p, [%0], %1;\n"
      "add.u32 n, n, 1;\nsetp.lt.and.u32 c, n, " SPIN_LIMIT ", !p;\n@c bra.uni WAIT;\n}"
      :
      : "r"(bar), "r"(parity)
      : "memory");
}
__device__ __forceinline__ void mbar_wait2(uint32_t a, uint32_t pa, uint32_t b, uint32_t pb) {
  asm volatile(
      "{\n.reg .pred p, q, c;\n.reg .u32 n;\nmov.u32 n, 0;\n"
      "WAIT:\nmbarrier.try_wait.parity.shared::cta.b64 p, [%0], %1;\nmbarrier.try_wait.parity.shared::cta.b64 q, [%2], %3;\n"
      "add.u32 n, n, 1;\nand.pred p, p, q;\nsetp.lt.and.u32 c, n, " SPIN_LIMIT ", !p;\n@c bra.uni WAIT;\n}"
      :
      : "r"(a), "r"(pa), "r"(b), "r"(pb)
      : "memory");
}
__device__ __forceinline__ void mbar_wait3(uint32_t a, uint32_t pa, uint32_t b, uint32_t pb, uint32_t d, uint32_t pd) {
  asm volatile(
      "{\n.reg .pred p, q, r, c;\n.reg .u32 n;\nmov.u32 n, 0;\n"
      "WAIT:\nmbarrier.try_wait.parity.shared::cta.b64 p, [%0], %1;\nmbarrier.try_wait.parity.shared::cta.b64 q, [%2], %3;\n"
      "mbarrier.try_wait.parity.shared::cta.b64 r, [%4], %5;\n"
      "add.u32 n, n, 1;\nand.pred p, p, q;\nand.pred p, p, r;\nsetp.lt.and.u32 c, n, " SPIN_LIMIT ", !p;\n@c bra.uni WAIT;\n}"
      :
      : "r"(a), "r"(pa), "r"(b), "r"(pb), "r"(d), "r"(pd)
      : "memory");
}
__device__ __forceinline__ void mbar_arrive_if(uint32_t bar, bool on) {
  asm volatile("{\n.reg .pred p;\nsetp.ne.u32 p, %1, 0;\n@p mbarrier.arrive.shared::cluster.b64 _, [%0];\n}" ::"r"(bar), "r"((uint32_t)on) : "memory");
}
__device__ __forceinline__ bool mbar_test(uint32_t bar, uint32_t parity) {
  uint32_t r;
  asm volatile("{\n.reg .pred p;\nmbarrier.test_wait.parity.shared::cta.b64 p, [%1], %2;\nselp.u32 %0, 1, 0, p;\n}"
               : "=r"(r) : "r"(bar), "r"(parity) : "memory");
  return r != 0;
}
__device__ __forceinline__ void poll_ge(const unsigned int* p, unsigned int target) {
  asm volatile(
      "{\n.reg .pred p, c;\n.reg .u32 n;\n.reg .s32 v;\nmov.u32 n, 0;\n"
      "POLL:\nld.relaxed.gpu.global.u32 v, [%0];\nsub.s32 v, v, %1;\nsetp.lt.s32 p, v, 0;\n"
      "add.u32 n, n, 1;\nsetp.lt.and.u32 c, n, " SPIN_LIMIT ", p;\n@c bra.uni POLL;\n}"
      :
      : "l"(p), "r"(target)
      : "memory");
}
__device__ __forceinline__ void signal_release(unsigned int* p, uint32_t v = 1) {
  asm volatile("red.release.gpu.global.add.u32 [%0], %1;" ::"l"(p), "r"(v) : "memory");
}
__device__ __forceinline__ void signal_relaxed(unsigned int* p, uint32_t v = 1) {
  asm volatile("red.relaxed.gpu.global.add.u32 [%0], %1;" ::"l"(p), "r"(v) : "memory");
}
__device__ __forceinline__ bool elect_one() {
  uint32_t pred;
  asm volatile("{\n.reg .pred p;\nelect.sync _|p, 0xffffffff;\nselp.u32 %0, 1, 0, p;\n}" : "=r"(pred));
  return pred != 0;
}
__device__ __forceinline__ void tma_load_2d(uint32_t dst, const CUtensorMap* map, uint32_t bar, int c0, int c1) {
  asm volatile(
      "cp.async.bulk.tensor.2d.shared::cluster.global.mbarrier::complete_tx::bytes [%0], [%1, {%3, %4}], [%2];" ::"r"(dst),
      "l"(map), "r"(bar), "r"(c0), "r"(c1)
      : "memory");
}
__device__ __forceinline__ void tma_load_3d(uint32_t dst, const CUtensorMap* map, uint32_t bar, int c0, int c1, int c2) {
  asm volatile(
      "cp.async.bulk.tensor.3d.shared::cluster.global.mbarrier::complete_tx::bytes [%0], [%1, {%3, %4, %5}], [%2];" ::"r"(dst),
      "l"(map), "r"(bar), "r"(c0), "r"(c1), "r"(c2)
      : "memory");
}
__device__ __forceinline__ void tma_load_3d_mc(uint32_t dst, const CUtensorMap* map, uint32_t bar, int c0, int c1, int c2) {
  asm volatile(
      "cp.async.bulk.tensor.3d.shared::cluster.global.mbarrier::complete_tx::bytes.multicast::cluster [%0], [%1, {%3, "
      "%4, %5}], [%2], %6;" ::"r"(dst),
      "l"(map), "r"(bar), "r"(c0), "r"(c1), "r"(c2), "h"((uint16_t)3)
      : "memory");
}
__device__ __forceinline__ void st_async_u4(uint32_t dst, uint32_t bar, uint32_t a, uint32_t b, uint32_t c, uint32_t d) {
  asm volatile("st.async.weak.shared::cluster.mbarrier::complete_tx::bytes.v4.b32 [%0], {%2, %3, %4, %5}, [%1];" ::"r"(dst),
               "r"(bar), "r"(a), "r"(b), "r"(c), "r"(d)
               : "memory");
}
__device__ __forceinline__ void tma_reduce_3d(const CUtensorMap* map, uint32_t src, int c0, int c1, int c2) {
  asm volatile("cp.reduce.async.bulk.tensor.3d.global.shared::cta.add.tile.bulk_group [%0, {%2, %3, %4}], [%1];" ::"l"(map),
               "r"(src), "r"(c0), "r"(c1), "r"(c2)
               : "memory");
}
__device__ __forceinline__ void tma_store_3d(const CUtensorMap* map, uint32_t src, int c0, int c1, int c2) {
  asm volatile("cp.async.bulk.tensor.3d.global.shared::cta.tile.bulk_group [%0, {%2, %3, %4}], [%1];" ::"l"(map), "r"(src),
               "r"(c0), "r"(c1), "r"(c2)
               : "memory");
}
__device__ __forceinline__ void tma_prefetch_2d(const CUtensorMap* map, int c0, int c1) {
  asm volatile("cp.async.bulk.prefetch.tensor.2d.L2.global.tile [%0, {%1, %2}];" ::"l"(map), "r"(c0), "r"(c1) : "memory");
}
__device__ __forceinline__ void prefetch_map(const CUtensorMap* map) {
  asm volatile("prefetch.tensormap [%0];" ::"l"(map) : "memory");
}
__device__ __forceinline__ void wgmma_fence() { asm volatile("wgmma.fence.sync.aligned;" ::: "memory"); }
__device__ __forceinline__ void wgmma_commit() { asm volatile("wgmma.commit_group.sync.aligned;" ::: "memory"); }
template <int N>
__device__ __forceinline__ void wgmma_wait() {
  asm volatile("wgmma.wait_group.sync.aligned %0;" ::"n"(N) : "memory");
}
__device__ __forceinline__ void named_bar_sync(int id, int nthreads) {
  asm volatile("bar.sync %0, %1;" ::"r"(id), "r"(nthreads) : "memory");
}
__device__ __forceinline__ void cluster_arrive_relaxed() { asm volatile("barrier.cluster.arrive.relaxed.aligned;" ::: "memory"); }
__device__ __forceinline__ void cluster_wait() { asm volatile("barrier.cluster.wait.acquire.aligned;" ::: "memory"); }
__device__ __forceinline__ uint32_t mapa(uint32_t addr, uint32_t rank) {
  uint32_t r;
  asm volatile("mapa.shared::cluster.u32 %0, %1, %2;" : "=r"(r) : "r"(addr), "r"(rank));
  return r;
}
__device__ __forceinline__ uint64_t desc_from_lo(uint32_t lo) { return (uint64_t)lo | (0x40000040ull << 32); }
__device__ __forceinline__ uint64_t desc_sbo(uint32_t lo, uint32_t sbo) { return (uint64_t)lo | ((0x40000000ull | (sbo >> 4)) << 32); }
__device__ __forceinline__ uint64_t desc_64(uint32_t lo) { return (uint64_t)lo | (0x80000020ull << 32); }
__device__ __forceinline__ uint32_t desc_lo_a(uint32_t addr) { return ((addr & 0x3FFFF) >> 4) | (1u << 16); }
__device__ __forceinline__ uint32_t desc_lo_b(uint32_t addr, uint32_t lbo_bytes) { return ((addr & 0x3FFFF) >> 4) | ((lbo_bytes >> 4) << 16); }
__device__ __forceinline__ uint32_t pack_bf16(float lo, float hi) {
  __nv_bfloat162 v = __floats2bfloat162_rn(lo, hi);
  return *reinterpret_cast<uint32_t*>(&v);
}
__device__ __forceinline__ float bf16r(float x) { return __uint_as_float(pack_bf16(0.f, x)); }
__device__ __forceinline__ float bf_lo(uint32_t u) { return __uint_as_float(u << 16); }
__device__ __forceinline__ float bf_hi(uint32_t u) { return __uint_as_float(u & 0xFFFF0000u); }
__device__ __forceinline__ uint4 lds_u4(uint32_t addr) {
  uint4 v;
  asm volatile("ld.shared.v4.b32 {%0, %1, %2, %3}, [%4];" : "=r"(v.x), "=r"(v.y), "=r"(v.z), "=r"(v.w) : "r"(addr) : "memory");
  return v;
}
__device__ __forceinline__ float2 lds_f2(uint32_t addr) {
  float2 v;
  asm volatile("ld.shared.v2.f32 {%0, %1}, [%2];" : "=f"(v.x), "=f"(v.y) : "r"(addr) : "memory");
  return v;
}
__device__ __forceinline__ void sts_f2(uint32_t addr, float a, float b) {
  asm volatile("st.shared.v2.f32 [%0], {%1, %2};" ::"r"(addr), "f"(a), "f"(b) : "memory");
}
__device__ __forceinline__ void sts_u4(uint32_t addr, uint32_t a, uint32_t b, uint32_t c, uint32_t d) {
  asm volatile("st.shared.v4.b32 [%0], {%1, %2, %3, %4};" ::"r"(addr), "r"(a), "r"(b), "r"(c), "r"(d) : "memory");
}
__device__ __forceinline__ void sts_u32(uint32_t addr, uint32_t v) { asm volatile("st.shared.b32 [%0], %1;" ::"r"(addr), "r"(v) : "memory"); }
__device__ __forceinline__ uint32_t lds_u32(uint32_t addr) {
  uint32_t v;
  asm volatile("ld.shared.b32 %0, [%1];" : "=r"(v) : "r"(addr) : "memory");
  return v;
}
__device__ __forceinline__ uint4 ldg_u4(const void* p, bool on = true) {
  uint4 v = make_uint4(0u, 0u, 0u, 0u);
  asm volatile("{\n.reg .pred p;\nsetp.ne.u32 p, %5, 0;\n@p ld.global.nc.L1::no_allocate.v4.b32 {%0, %1, %2, %3}, [%4];\n}"
               : "+r"(v.x), "+r"(v.y), "+r"(v.z), "+r"(v.w) : "l"(p), "r"((uint32_t)on) : "memory");
  return v;
}
__device__ __forceinline__ float4 ldg_cg_f4(const void* p) {
  float4 v;
  asm volatile("ld.global.cg.v4.f32 {%0, %1, %2, %3}, [%4];" : "=f"(v.x), "=f"(v.y), "=f"(v.z), "=f"(v.w) : "l"(p) : "memory");
  return v;
}
__device__ __forceinline__ void st_tagged(void* p, uint32_t a, uint32_t b, uint32_t c, uint32_t tag) {
  asm volatile("{\n.reg .b64 l, h;\n.reg .b128 v;\nmov.b64 l, {%1, %2};\nmov.b64 h, {%3, %4};\nmov.b128 v, {l, h};\n"
               "st.relaxed.gpu.global.b128 [%0], v;\n}" ::"l"(p), "r"(a), "r"(b), "r"(c), "r"(tag) : "memory");
}
__device__ __forceinline__ void st_tagged_any(uint64_t p, uint32_t a, uint32_t b, uint32_t c, uint32_t tag) {
  asm volatile("{\n.reg .b64 l, h;\n.reg .b128 v;\nmov.b64 l, {%1, %2};\nmov.b64 h, {%3, %4};\nmov.b128 v, {l, h};\n"
               "st.relaxed.gpu.b128 [%0], v;\n}" ::"l"(p), "r"(a), "r"(b), "r"(c), "r"(tag) : "memory");
}
__device__ __forceinline__ uint4 ld_tagged(const void* p) {
  uint4 r;
  asm volatile("{\n.reg .b64 l, h;\n.reg .b128 v;\nld.relaxed.gpu.global.b128 v, [%4];\nmov.b128 {l, h}, v;\n"
               "mov.b64 {%0, %1}, l;\nmov.b64 {%2, %3}, h;\n}" : "=r"(r.x), "=r"(r.y), "=r"(r.z), "=r"(r.w) : "l"(p) : "memory");
  return r;
}
__device__ __forceinline__ void cp_async16(uint32_t dst, const void* src) {
  asm volatile("cp.async.cg.shared.global [%0], [%1], 16;" ::"r"(dst), "l"(src) : "memory");
}
__device__ __forceinline__ void cp_async_arrive(uint32_t bar) {
  asm volatile("cp.async.mbarrier.arrive.shared::cta.b64 [%0];" ::"r"(bar) : "memory");
}
__device__ __forceinline__ void bulk_store(void* gdst, uint32_t src, uint32_t bytes) {
  asm volatile("cp.async.bulk.global.shared::cta.bulk_group [%0], [%1], %2;" ::"l"(gdst), "r"(src), "r"(bytes) : "memory");
}
__device__ __forceinline__ void bulk_load(uint32_t dst, const void* gsrc, uint32_t bytes, uint32_t bar) {
  asm volatile("cp.async.bulk.shared::cluster.global.mbarrier::complete_tx::bytes [%0], [%1], %2, [%3];" ::"r"(dst), "l"(gsrc),
               "r"(bytes), "r"(bar)
               : "memory");
}
__device__ __forceinline__ void bulk_commit() { asm volatile("cp.async.bulk.commit_group;" ::: "memory"); }
template <int N>
__device__ __forceinline__ void bulk_wait() { asm volatile("cp.async.bulk.wait_group %0;" ::"n"(N) : "memory"); }
__device__ __forceinline__ void stsm_x4(uint32_t addr, uint32_t a, uint32_t b, uint32_t c, uint32_t d) {
  asm volatile("stmatrix.sync.aligned.m8n8.x4.shared.b16 [%0], {%1, %2, %3, %4};" ::"r"(addr), "r"(a), "r"(b), "r"(c), "r"(d) : "memory");
}
__device__ __forceinline__ uint32_t movm(uint32_t a) {
  uint32_t d;
  asm volatile("movmatrix.sync.aligned.m8n8.trans.b16 %0, %1;" : "=r"(d) : "r"(a));
  return d;
}
__device__ __forceinline__ void mma_16816(float (&d)[4], uint32_t a0, uint32_t a1, uint32_t a2, uint32_t a3, uint32_t b0, uint32_t b1) {
  asm volatile("mma.sync.aligned.m16n8k16.row.col.f32.bf16.bf16.f32 {%0, %1, %2, %3}, {%4, %5, %6, %7}, {%8, %9}, {%0, %1, %2, %3};"
               : "+f"(d[0]), "+f"(d[1]), "+f"(d[2]), "+f"(d[3]) : "r"(a0), "r"(a1), "r"(a2), "r"(a3), "r"(b0), "r"(b1));
}
__device__ __forceinline__ void mma_16816_z(float (&d)[4], uint32_t a0, uint32_t a1, uint32_t a2, uint32_t a3, uint32_t b0, uint32_t b1) {
  asm volatile("mma.sync.aligned.m16n8k16.row.col.f32.bf16.bf16.f32 {%0, %1, %2, %3}, {%4, %5, %6, %7}, {%8, %9}, {%10, %10, %10, %10};"
               : "=f"(d[0]), "=f"(d[1]), "=f"(d[2]), "=f"(d[3]) : "r"(a0), "r"(a1), "r"(a2), "r"(a3), "r"(b0), "r"(b1), "f"(0.f));
}
__device__ __forceinline__ void mma_1688(float (&d)[4], uint32_t a0, uint32_t a1, uint32_t b0) {
  asm volatile("mma.sync.aligned.m16n8k8.row.col.f32.bf16.bf16.f32 {%0, %1, %2, %3}, {%4, %5}, {%6}, {%7, %7, %7, %7};"
               : "=f"(d[0]), "=f"(d[1]), "=f"(d[2]), "=f"(d[3]) : "r"(a0), "r"(a1), "r"(b0), "f"(0.f));
}
__device__ __forceinline__ void fence_proxy_async() { asm volatile("fence.proxy.async.shared::cta;" ::: "memory"); }

template<int N> __device__ __forceinline__ void wgmma_ss(float (&d)[N/2], uint64_t descA, uint64_t descB, int scaleD);
template<int N> __device__ __forceinline__ void wgmma_rs(float (&d)[N/2], uint32_t a0, uint32_t a1, uint32_t a2, uint32_t a3, uint64_t descB, int scaleD);
template<> __device__ __forceinline__ void wgmma_ss<64>(float (&d)[32], uint64_t descA, uint64_t descB, int scaleD) {
  asm volatile("{\n.reg .pred p;\nsetp.ne.b32 p, %34, 0;\n"
    "wgmma.mma_async.sync.aligned.m64n64k16.f32.bf16.bf16 {%0, %1, %2, %3, %4, %5, %6, %7, %8, %9, %10, %11, %12, %13, %14, %15, %16, %17, %18, %19, %20, %21, %22, %23, %24, %25, %26, %27, %28, %29, %30, %31}, %32, %33, p, 1, 1, 0, 1;\n}\n"
    : "+f"(d[0]), "+f"(d[1]), "+f"(d[2]), "+f"(d[3]), "+f"(d[4]), "+f"(d[5]), "+f"(d[6]), "+f"(d[7]), "+f"(d[8]), "+f"(d[9]), "+f"(d[10]), "+f"(d[11]), "+f"(d[12]), "+f"(d[13]), "+f"(d[14]), "+f"(d[15]), "+f"(d[16]), "+f"(d[17]), "+f"(d[18]), "+f"(d[19]), "+f"(d[20]), "+f"(d[21]), "+f"(d[22]), "+f"(d[23]), "+f"(d[24]), "+f"(d[25]), "+f"(d[26]), "+f"(d[27]), "+f"(d[28]), "+f"(d[29]), "+f"(d[30]), "+f"(d[31])
    : "l"(descA), "l"(descB), "r"(scaleD));
}
template<> __device__ __forceinline__ void wgmma_ss<128>(float (&d)[64], uint64_t descA, uint64_t descB, int scaleD) {
  asm volatile("{\n.reg .pred p;\nsetp.ne.b32 p, %66, 0;\n"
    "wgmma.mma_async.sync.aligned.m64n128k16.f32.bf16.bf16 {%0, %1, %2, %3, %4, %5, %6, %7, %8, %9, %10, %11, %12, %13, %14, %15, %16, %17, %18, %19, %20, %21, %22, %23, %24, %25, %26, %27, %28, %29, %30, %31, %32, %33, %34, %35, %36, %37, %38, %39, %40, %41, %42, %43, %44, %45, %46, %47, %48, %49, %50, %51, %52, %53, %54, %55, %56, %57, %58, %59, %60, %61, %62, %63}, %64, %65, p, 1, 1, 0, 1;\n}\n"
    : "+f"(d[0]), "+f"(d[1]), "+f"(d[2]), "+f"(d[3]), "+f"(d[4]), "+f"(d[5]), "+f"(d[6]), "+f"(d[7]), "+f"(d[8]), "+f"(d[9]), "+f"(d[10]), "+f"(d[11]), "+f"(d[12]), "+f"(d[13]), "+f"(d[14]), "+f"(d[15]), "+f"(d[16]), "+f"(d[17]), "+f"(d[18]), "+f"(d[19]), "+f"(d[20]), "+f"(d[21]), "+f"(d[22]), "+f"(d[23]), "+f"(d[24]), "+f"(d[25]), "+f"(d[26]), "+f"(d[27]), "+f"(d[28]), "+f"(d[29]), "+f"(d[30]), "+f"(d[31]), "+f"(d[32]), "+f"(d[33]), "+f"(d[34]), "+f"(d[35]), "+f"(d[36]), "+f"(d[37]), "+f"(d[38]), "+f"(d[39]), "+f"(d[40]), "+f"(d[41]), "+f"(d[42]), "+f"(d[43]), "+f"(d[44]), "+f"(d[45]), "+f"(d[46]), "+f"(d[47]), "+f"(d[48]), "+f"(d[49]), "+f"(d[50]), "+f"(d[51]), "+f"(d[52]), "+f"(d[53]), "+f"(d[54]), "+f"(d[55]), "+f"(d[56]), "+f"(d[57]), "+f"(d[58]), "+f"(d[59]), "+f"(d[60]), "+f"(d[61]), "+f"(d[62]), "+f"(d[63])
    : "l"(descA), "l"(descB), "r"(scaleD));
}
template<> __device__ __forceinline__ void wgmma_ss<216>(float (&d)[108], uint64_t descA, uint64_t descB, int scaleD) {
  asm volatile("{\n.reg .pred p;\nsetp.ne.b32 p, %110, 0;\n"
    "wgmma.mma_async.sync.aligned.m64n216k16.f32.bf16.bf16 {%0, %1, %2, %3, %4, %5, %6, %7, %8, %9, %10, %11, %12, %13, %14, %15, %16, %17, %18, %19, %20, %21, %22, %23, %24, %25, %26, %27, %28, %29, %30, %31, %32, %33, %34, %35, %36, %37, %38, %39, %40, %41, %42, %43, %44, %45, %46, %47, %48, %49, %50, %51, %52, %53, %54, %55, %56, %57, %58, %59, %60, %61, %62, %63, %64, %65, %66, %67, %68, %69, %70, %71, %72, %73, %74, %75, %76, %77, %78, %79, %80, %81, %82, %83, %84, %85, %86, %87, %88, %89, %90, %91, %92, %93, %94, %95, %96, %97, %98, %99, %100, %101, %102, %103, %104, %105, %106, %107}, %108, %109, p, 1, 1, 0, 1;\n}\n"
    : "+f"(d[0]), "+f"(d[1]), "+f"(d[2]), "+f"(d[3]), "+f"(d[4]), "+f"(d[5]), "+f"(d[6]), "+f"(d[7]), "+f"(d[8]), "+f"(d[9]), "+f"(d[10]), "+f"(d[11]), "+f"(d[12]), "+f"(d[13]), "+f"(d[14]), "+f"(d[15]), "+f"(d[16]), "+f"(d[17]), "+f"(d[18]), "+f"(d[19]), "+f"(d[20]), "+f"(d[21]), "+f"(d[22]), "+f"(d[23]), "+f"(d[24]), "+f"(d[25]), "+f"(d[26]), "+f"(d[27]), "+f"(d[28]), "+f"(d[29]), "+f"(d[30]), "+f"(d[31]), "+f"(d[32]), "+f"(d[33]), "+f"(d[34]), "+f"(d[35]), "+f"(d[36]), "+f"(d[37]), "+f"(d[38]), "+f"(d[39]), "+f"(d[40]), "+f"(d[41]), "+f"(d[42]), "+f"(d[43]), "+f"(d[44]), "+f"(d[45]), "+f"(d[46]), "+f"(d[47]), "+f"(d[48]), "+f"(d[49]), "+f"(d[50]), "+f"(d[51]), "+f"(d[52]), "+f"(d[53]), "+f"(d[54]), "+f"(d[55]), "+f"(d[56]), "+f"(d[57]), "+f"(d[58]), "+f"(d[59]), "+f"(d[60]), "+f"(d[61]), "+f"(d[62]), "+f"(d[63]), "+f"(d[64]), "+f"(d[65]), "+f"(d[66]), "+f"(d[67]), "+f"(d[68]), "+f"(d[69]), "+f"(d[70]), "+f"(d[71]), "+f"(d[72]), "+f"(d[73]), "+f"(d[74]), "+f"(d[75]), "+f"(d[76]), "+f"(d[77]), "+f"(d[78]), "+f"(d[79]), "+f"(d[80]), "+f"(d[81]), "+f"(d[82]), "+f"(d[83]), "+f"(d[84]), "+f"(d[85]), "+f"(d[86]), "+f"(d[87]), "+f"(d[88]), "+f"(d[89]), "+f"(d[90]), "+f"(d[91]), "+f"(d[92]), "+f"(d[93]), "+f"(d[94]), "+f"(d[95]), "+f"(d[96]), "+f"(d[97]), "+f"(d[98]), "+f"(d[99]), "+f"(d[100]), "+f"(d[101]), "+f"(d[102]), "+f"(d[103]), "+f"(d[104]), "+f"(d[105]), "+f"(d[106]), "+f"(d[107])
    : "l"(descA), "l"(descB), "r"(scaleD));
}
template<> __device__ __forceinline__ void wgmma_rs<64>(float (&d)[32], uint32_t a0, uint32_t a1, uint32_t a2, uint32_t a3, uint64_t descB, int scaleD) {
  asm volatile("{\n.reg .pred p;\nsetp.ne.b32 p, %37, 0;\n"
    "wgmma.mma_async.sync.aligned.m64n64k16.f32.bf16.bf16 {%0, %1, %2, %3, %4, %5, %6, %7, %8, %9, %10, %11, %12, %13, %14, %15, %16, %17, %18, %19, %20, %21, %22, %23, %24, %25, %26, %27, %28, %29, %30, %31}, {%32, %33, %34, %35}, %36, p, 1, 1, 1;\n}\n"
    : "+f"(d[0]), "+f"(d[1]), "+f"(d[2]), "+f"(d[3]), "+f"(d[4]), "+f"(d[5]), "+f"(d[6]), "+f"(d[7]), "+f"(d[8]), "+f"(d[9]), "+f"(d[10]), "+f"(d[11]), "+f"(d[12]), "+f"(d[13]), "+f"(d[14]), "+f"(d[15]), "+f"(d[16]), "+f"(d[17]), "+f"(d[18]), "+f"(d[19]), "+f"(d[20]), "+f"(d[21]), "+f"(d[22]), "+f"(d[23]), "+f"(d[24]), "+f"(d[25]), "+f"(d[26]), "+f"(d[27]), "+f"(d[28]), "+f"(d[29]), "+f"(d[30]), "+f"(d[31])
    : "r"(a0), "r"(a1), "r"(a2), "r"(a3), "l"(descB), "r"(scaleD));
}
template<> __device__ __forceinline__ void wgmma_rs<216>(float (&d)[108], uint32_t a0, uint32_t a1, uint32_t a2, uint32_t a3, uint64_t descB, int scaleD) {
  asm volatile("{\n.reg .pred p;\nsetp.ne.b32 p, %113, 0;\n"
    "wgmma.mma_async.sync.aligned.m64n216k16.f32.bf16.bf16 {%0, %1, %2, %3, %4, %5, %6, %7, %8, %9, %10, %11, %12, %13, %14, %15, %16, %17, %18, %19, %20, %21, %22, %23, %24, %25, %26, %27, %28, %29, %30, %31, %32, %33, %34, %35, %36, %37, %38, %39, %40, %41, %42, %43, %44, %45, %46, %47, %48, %49, %50, %51, %52, %53, %54, %55, %56, %57, %58, %59, %60, %61, %62, %63, %64, %65, %66, %67, %68, %69, %70, %71, %72, %73, %74, %75, %76, %77, %78, %79, %80, %81, %82, %83, %84, %85, %86, %87, %88, %89, %90, %91, %92, %93, %94, %95, %96, %97, %98, %99, %100, %101, %102, %103, %104, %105, %106, %107}, {%108, %109, %110, %111}, %112, p, 1, 1, 1;\n}\n"
    : "+f"(d[0]), "+f"(d[1]), "+f"(d[2]), "+f"(d[3]), "+f"(d[4]), "+f"(d[5]), "+f"(d[6]), "+f"(d[7]), "+f"(d[8]), "+f"(d[9]), "+f"(d[10]), "+f"(d[11]), "+f"(d[12]), "+f"(d[13]), "+f"(d[14]), "+f"(d[15]), "+f"(d[16]), "+f"(d[17]), "+f"(d[18]), "+f"(d[19]), "+f"(d[20]), "+f"(d[21]), "+f"(d[22]), "+f"(d[23]), "+f"(d[24]), "+f"(d[25]), "+f"(d[26]), "+f"(d[27]), "+f"(d[28]), "+f"(d[29]), "+f"(d[30]), "+f"(d[31]), "+f"(d[32]), "+f"(d[33]), "+f"(d[34]), "+f"(d[35]), "+f"(d[36]), "+f"(d[37]), "+f"(d[38]), "+f"(d[39]), "+f"(d[40]), "+f"(d[41]), "+f"(d[42]), "+f"(d[43]), "+f"(d[44]), "+f"(d[45]), "+f"(d[46]), "+f"(d[47]), "+f"(d[48]), "+f"(d[49]), "+f"(d[50]), "+f"(d[51]), "+f"(d[52]), "+f"(d[53]), "+f"(d[54]), "+f"(d[55]), "+f"(d[56]), "+f"(d[57]), "+f"(d[58]), "+f"(d[59]), "+f"(d[60]), "+f"(d[61]), "+f"(d[62]), "+f"(d[63]), "+f"(d[64]), "+f"(d[65]), "+f"(d[66]), "+f"(d[67]), "+f"(d[68]), "+f"(d[69]), "+f"(d[70]), "+f"(d[71]), "+f"(d[72]), "+f"(d[73]), "+f"(d[74]), "+f"(d[75]), "+f"(d[76]), "+f"(d[77]), "+f"(d[78]), "+f"(d[79]), "+f"(d[80]), "+f"(d[81]), "+f"(d[82]), "+f"(d[83]), "+f"(d[84]), "+f"(d[85]), "+f"(d[86]), "+f"(d[87]), "+f"(d[88]), "+f"(d[89]), "+f"(d[90]), "+f"(d[91]), "+f"(d[92]), "+f"(d[93]), "+f"(d[94]), "+f"(d[95]), "+f"(d[96]), "+f"(d[97]), "+f"(d[98]), "+f"(d[99]), "+f"(d[100]), "+f"(d[101]), "+f"(d[102]), "+f"(d[103]), "+f"(d[104]), "+f"(d[105]), "+f"(d[106]), "+f"(d[107])
    : "r"(a0), "r"(a1), "r"(a2), "r"(a3), "l"(descB), "r"(scaleD));
}

constexpr int TILE = 8192, HALF = 9 * TILE;
constexpr int SLOT = 16384;
constexpr int RING = 2 * HALF;
constexpr int OVF = RING + 5 * SLOT;
constexpr int TAB = OVF + 1024;
constexpr int BARS = TAB + 1024;
constexpr int SMEM_BYTES = BARS + 1024;
constexpr int WOA = 9216;
constexpr int B_FULL = BARS, B_FX = BARS + 56, B_AUX = BARS + 200, B_NB = BARS + 208, B_ROLE = BARS + 272, B_S1 = BARS + 280,
              B_ST = BARS + 288, B_EMPTY = BARS + 432, B_J = BARS + 488, B_XF = BARS + 496,
              B_QK = BARS + 504, B_RX = BARS + 512, B_SR = BARS + 528, B_OX = BARS + 536, B_HP = BARS + 552;
constexpr int S_ROLE = BARS + 568, S_EP = BARS + 572, S_WS = BARS + 576;

template <int V>
struct IC {
  static constexpr int value = V;
};
struct Maps {
  CUtensorMap x0, r, wq, wo, wg, wu, wd, tg, tu, hg, hu;
};

#define TA0(i)
#define TA(i)
#define TS(i)
#define TR(i)

__device__ __forceinline__ int tid_now() {
  int t;
  asm volatile("mov.u32 %0, %%tid.x;" : "=r"(t));
  return t;
}
__device__ __forceinline__ float quad_sum(float v) {
  v += __shfl_xor_sync(0xffffffffu, v, 1);
  return v + __shfl_xor_sync(0xffffffffu, v, 2);
}
__device__ __forceinline__ float inv_sd(float var) {
  float s, r;
  asm("sqrt.approx.ftz.f32 %0, %1;" : "=f"(s) : "f"(bf16r(bf16r(fmaxf(var, 0.f)) + 1e-5f)));
  asm("rcp.approx.ftz.f32 %0, %1;" : "=f"(r) : "f"(bf16r(s)));
  return r;
}
__device__ __forceinline__ float sum8(const uint4& v) {
  return ((bf_lo(v.x) + bf_hi(v.x)) + (bf_lo(v.y) + bf_hi(v.y))) + ((bf_lo(v.z) + bf_hi(v.z)) + (bf_lo(v.w) + bf_hi(v.w)));
}
__device__ __forceinline__ void warp_arrive(uint32_t bar) {
  __syncwarp();
  if ((tid_now() & 31) == 0) mbar_arrive(bar);
}
__device__ __forceinline__ void release_slot(uint32_t sb, int p, bool on = true) {
  asm volatile("{\n.reg .pred p;\nsetp.eq.u32 p, %1, 0;\n@p mbarrier.arrive.shared::cta.b64 _, [%0];\n}" ::"r"(sb + B_EMPTY + 8 * p),
               "r"((tid_now() & 31) | (on ? 0 : 1))
               : "memory");
}
__device__ __forceinline__ uint32_t stage_addr(uint32_t sb) {
  const int tid = tid_now(), lane = tid & 31;
  return sb + (tid >> 7) * HALF + ((tid >> 5) & 3) * 2048 + (lane & 15) * 128 + (((lane >> 4) ^ (lane & 7)) << 4);
}
__device__ __forceinline__ void stage_done(uint32_t sb, int a, int n) {
    __syncwarp();
  const int tid = tid_now();
  if ((tid & 31) < n) mbar_arrive(sb + B_ST + 72 * (tid >> 7) + 8 * (a + (tid & 31)));
}
template <int I0 = 0, int I1 = 4>
__device__ __forceinline__ void stage_tile(const float (&acc)[32], float m0, float c0, float m1, float c1, uint32_t sb, int a, int b, int n) {
  const uint32_t ad = stage_addr(sb) + a * TILE;
#pragma unroll
  for (int i = I0; i < I1; ++i)
    stsm_x4(ad ^ (i << 5), pack_bf16(fmaf(acc[8 * i], m0, c0), fmaf(acc[8 * i + 1], m0, c0)),
            pack_bf16(fmaf(acc[8 * i + 2], m1, c1), fmaf(acc[8 * i + 3], m1, c1)),
            pack_bf16(fmaf(acc[8 * i + 4], m0, c0), fmaf(acc[8 * i + 5], m0, c0)),
            pack_bf16(fmaf(acc[8 * i + 6], m1, c1), fmaf(acc[8 * i + 7], m1, c1)));
  if (n) stage_done(sb, b, n);
}

#define NLAYERS 2
#define X_EARLY 2
#define X_SCHED 0x1111111ull
#define PACE 2800
#define X_PF 0
#define DN_LATE 0
#define ST_END 5
#define GU_PF0 16
#define GU_PFN 16
#define R0_N 0
#define R1_N 2
#define PACE_R 1400
#define PACE0 4500
#define IMG 1
#define GU_PRE 1
#define Q_H 8
#define LAZY 1
#define Q_ST0 7
#define KH 4
#define H_DELAY 4000
#define H_SLEEP 100
#define PFM 1
#define T_HOLD 8
#define T_LEAD 8
#define DN_PF 1
#define DN_NS 200
#define Q_ST1 6

__global__ void __cluster_dims__(2, 1, 1) __launch_bounds__(384, 1)
mega_kernel(const __grid_constant__ Maps mp, const __nv_bfloat16* __restrict__ x0, const __nv_bfloat16* __restrict__ wqkv,
            const __nv_bfloat16* __restrict__ wo, __nv_bfloat16* __restrict__ out, int small_gpc) {
  extern __shared__ __align__(1024) uint8_t smem[];
  const uint32_t sb = smem_u32(smem);
  const uint32_t rank = blockIdx.x & 1;
  const int warp = __shfl_sync(0xffffffffu, threadIdx.x >> 5, 0);
  TA0(63);
  if (warp != 8) {
    if (elect_one()) {
      const uint32_t b0 = sb + BARS + 48 * (warp - (warp > 8));
      if (warp < 11) {
#pragma unroll
        for (int i = 0; i < 6; ++i) mbar_init(b0 + 8 * i, warp < 6 ? 1 : warp < 10 ? 4 : 8);
        if (warp == 5) mbar_expect_tx(sb + B_ROLE, 4);
      } else {
#pragma unroll
        for (int i = 0; i < 11; ++i) mbar_init(b0 + 8 * i, i < 3 ? 8 : i < 6 ? 4 : i < 7 ? 2 : 1);
      }
      asm volatile("fence.mbarrier_init.release.cluster;" ::: "memory");
      if (warp == 9) prefetch_map(&mp.x0);
      if (warp == 10) prefetch_map(&mp.wq);
    }
  }
  __syncwarp();
  cluster_arrive_relaxed();
  uint32_t pr, ep1 = 0;
  asm volatile("mov.u32 %0, %%smid;" : "=r"(pr));
  pr >>= 1;
  pr = !small_gpc ? (pr < 64 ? pr & 7 : 8) : pr < 32 ? pr & 7 : pr < 60 ? 1 + (pr - 32) % 7 : pr < 62 ? 8 : 0;
  asm volatile("{\n.reg .pred p, q;\nsetp.eq.u32 p, %3, 256;\nsetp.ge.u32 q, %3, 288;\n"
               "@p atom.relaxed.gpu.global.inc.u32 %0, [%1], 0x7fffffff;\n@q ld.relaxed.gpu.global.u32 %0, [%2];\n}"
               : "+r"(ep1)
               : "l"(&gs_.claim[pr]), "l"(&gs_.epoch[blockIdx.x]), "r"(threadIdx.x | rank)
               : "memory");
  TA0(2);

  if (warp >= 8) {
    asm volatile("setmaxnreg.dec.sync.aligned.u32 24;");
    int j, rb;
    auto start = [&]() {
      mbar_wait(sb + B_ROLE, 0);
      const int role = __shfl_sync(0xffffffffu, lds_u32(sb + S_ROLE), 0);
      j = (role & 3) * 2 + rank;
      rb = role >> 2;
      ep1 = __shfl_sync(0xffffffffu, ep1, 0) + 1;
      TA0(59);
    };
    auto load_wq = [&](uint32_t dst, uint32_t bar, int s) {
      const int lane = tid_now() & 31;
      const __nv_bfloat16* src = wqkv + (32 * s + lane) * NQKV + 72 * j + (rank ? 0 : 64);
      if (elect_one()) tma_load_3d(dst, &mp.wq, bar, 72 * j + 8 * rank, 32 * s, 0);
#pragma unroll
      for (int c = 0; c < 3; ++c) cp_async16(dst + 12288 + lane * 128 + ((c ^ (lane & 7)) << 4), src + c * 576);
      cp_async_arrive(bar);
      __syncwarp();
      if (elect_one()) mbar_expect_tx(bar, 12288);
    };
    auto load_halves = [&](uint32_t dst, uint32_t bar, int c0, int c1, int cy) {
      if (elect_one()) tma_load_2d(dst, &mp.hg, bar, c0, cy);
      if (elect_one()) tma_load_2d(dst + 4096, &mp.hg, bar, c1, cy);
      if (elect_one()) tma_load_2d(dst + 8192, &mp.hu, bar, c0, cy);
      if (elect_one()) tma_load_2d(dst + 12288, &mp.hu, bar, c1, cy);
    };
    auto publish = [&](bool tell) {
      sts_u32(sb + S_EP, ep1);
      TA0(10);
        const int lane = tid_now() & 31;
        mbar_wait(sb + B_J, 0);
        float2 c = make_float2(0.f, 0.f);
#pragma unroll
        for (int w = 0; w < 8; ++w) {
          const float2 v = lds_f2(sb + OVF + w * 256 + lane * 8);
          c.x += v.x;
          c.y += v.y;
        }
        if (blockIdx.x < 108) *reinterpret_cast<float2*>(gs_.csq + (blockIdx.x & 3) * NQKV + (blockIdx.x >> 2) * 64 + 2 * lane) = c;
        if (tell) asm volatile("bar.arrive 6, 96;" ::: "memory");
        if (elect_one()) signal_release(&gs_.flag[FL_J]);
        TA0(11);
        poll_ge(&gs_.flag[FL_J], ep1 * NCTA);
        TA0(12);
        if (blockIdx.x == 0 && lane < 9) gs_.claim[lane] = 0u;
    };
    if (warp == 8) {
      cluster_wait();
      if (rank == 0) {
        uint32_t claim = __shfl_sync(0xffffffffu, ep1, 0);
#pragma unroll 1
        for (int i = 0; i < 8 && claim >= (pr == 8 ? 2 : 8); ++i) {
          pr = pr == 8 ? 0 : pr + 1;
          if (tid_now() == 256) asm volatile("atom.relaxed.gpu.global.inc.u32 %0, [%1], 0x7fffffff;" : "=r"(claim) : "l"(&gs_.claim[pr]) : "memory");
          claim = __shfl_sync(0xffffffffu, claim, 0);
        }
        claim = ((pr >> 2) * 8 + (claim & 7)) * 4 + (pr & 3);
        const uint32_t r = tid_now() & 31;
        if (r < 2)
          asm volatile("st.async.weak.shared::cluster.mbarrier::complete_tx::bytes.u32 [%0], %1, [%2];" ::"r"(mapa(sb + S_ROLE, r)),
                       "r"(claim), "r"(mapa(sb + B_ROLE, r))
                       : "memory");
        __syncwarp();
      }
      start();
      if (rb >= 16) {
        int p = 2;
        uint32_t ph = 1;
        named_bar_sync(6, 96);
#pragma unroll 1
        for (int n = 0, s = 0; n < 72 * NLAYERS; ++n) {
          const uint32_t bar = sb + B_FULL + 8 * p;
          mbar_wait(bar + (B_EMPTY - B_FULL), ph);
          if (elect_one()) {
            bulk_load(sb + RING + p * SLOT, gs_.himg + s * 1024, SLOT, bar);
            mbar_expect_tx(bar, SLOT);
          }
          if (n % 72 < 26) s += s < 18 ? 9 : -17;
          else if (++s == 36) s = 0;
          if (++p == 5) p = 0;
          if (p == 2) ph ^= 1;
        }
      } else {
      int p = 2;
      uint32_t ph = 1;
      const int f0 = j * 576;
      int xi = X_EARLY;
#pragma unroll 1
      for (int L = 0; L < NLAYERS; ++L) {
#pragma unroll 1
        for (int s = 0; s < 18; ++s) {
          const uint32_t bar = sb + B_FULL + 8 * p;
          mbar_wait(bar + (B_EMPTY - B_FULL), ph);
          TR(s);
          if (L == 0 || !IMG) {
            load_wq(sb + RING + p * SLOT, bar, s);
            if (L == 0 && elect_one()) {
#pragma unroll 1
              for (int e = (X_SCHED >> (2 * s)) & 3; e > 0; --e, ++xi)
                tma_load_3d_mc(sb + rank * HALF + xi * TILE, &mp.x0, sb + B_FX + 72 * rank + 8 * xi, xi * 64, rb * 64 + rank * 32, 0);
              const int u = (s - GU_PF0) * 8 + (rb >> 1);
              if (s >= GU_PF0 && u < GU_PFN) tma_prefetch_2d((rb & 1) ? &mp.wu : &mp.wg, f0 + 64 * (u % 3), 64 * (u / 3));
            }
          } else if (elect_one()) {
            bulk_load(sb + RING + p * SLOT, gs_.wimg + (j * 18 + s) * 1024, SLOT, bar);
            mbar_expect_tx(bar, SLOT);
          }
          if (++p == 5) p = 0;
          if (p == 2) ph ^= 1;
        }
#pragma unroll 1
        for (int s = 0; s < 5; ++s) {
          const int cx = s ? 64 * (2 * s - 1 + rank) : 0;
          mbar_wait(sb + B_EMPTY + 8 * s, ph);
          if (elect_one()) {
            if (s) tma_load_2d(sb + RING + (2 * s - 1) * WOA, &mp.wo, sb + B_FULL + 8 * s, cx, 72 * j);
            tma_load_2d(sb + RING + 2 * s * WOA, &mp.wo, sb + B_FULL + 8 * s, cx, 72 * (s ? j ^ 1 : j));
            mbar_expect_tx(sb + B_FULL + 8 * s, s ? 2 * WOA : WOA);
          }
          if (s == 1) ph ^= 1;
        }
        {
          int cx = f0, cy = 0;
          if (PFM && elect_one()) {
            prefetch_map(&mp.tg);
            prefetch_map(&mp.tu);
            prefetch_map(&mp.wd);
          }
#pragma unroll 1
          for (int n = 0; n < 72; ++n) {
            const uint32_t dst = sb + RING + p * SLOT, bar = sb + B_FULL + 8 * p;
            if (n == (rank ? R1_N : R0_N)) {
              mbar_wait(sb + B_ST + 72 + 8, 0);
              fence_proxy_async();
              if (elect_one()) tma_reduce_3d(&mp.r, sb + HALF + (1 + rank) * TILE, 64 + 64 * rank, rb * 64 + 32, 0);
              bulk_commit();
              if (!rank) {
                bulk_wait<0>();
                asm volatile("bar.arrive 8, 64;" ::: "memory");
              }
              mbar_wait(sb + B_ST + 8, 0);
              fence_proxy_async();
              if (elect_one()) tma_reduce_3d(&mp.r, sb + (1 + rank) * TILE, 64 + 64 * rank, rb * 64, 0);
              bulk_commit();
            }
            mbar_wait(bar + (B_EMPTY - B_FULL), ph);
            if (elect_one()) tma_load_2d(dst, &mp.wg, bar, cx, cy);
            if (elect_one()) tma_load_2d(dst + 8192, &mp.wu, bar, cx, cy);
            if (elect_one()) mbar_expect_tx(bar, 16384);
            if (n == (rank ? R1_N : R0_N)) {
              bulk_wait<0>();
              if (rank) asm volatile("bar.arrive 8, 64;" ::: "memory");
              asm volatile("bar.arrive 7, 64;" ::: "memory");
            }
            if (n < 26) {
              cx += 64;
              if (cx == f0 + 192) {
                cx = f0;
                cy += 64;
              }
            } else if ((cy += 64) == 576) {
              cy = 0;
              cx += 64;
            }
            if (++p == 5) p = 0;
            if (p == 2) ph ^= 1;
          }
        }
#pragma unroll 1
        for (int cy = 0; cy < 576; cy += 64) {
          const uint32_t dst = sb + RING + p * SLOT, bar = sb + B_FULL + 8 * p;
          mbar_wait(bar + (B_EMPTY - B_FULL), ph);
          if (elect_one()) tma_load_3d(dst, &mp.tg, bar, 0, cy, 18 * j + 16);
          if (elect_one()) tma_load_3d(dst + 8192, &mp.tu, bar, 0, cy, 18 * j + 16);
          if (elect_one()) mbar_expect_tx(bar, 16384);
          if (++p == 5) p = 0;
          if (p == 2) ph ^= 1;
        }
        {
          int cx = 0, cy = f0;
#pragma unroll 1
          for (int n = 35; n > -6; --n) {
            const uint32_t dst = p < 5 ? sb + RING + p * SLOT : sb + 2 * TILE + p * TILE, bar = sb + B_FULL + 8 * p;
            mbar_wait(bar + (B_EMPTY - B_FULL), ph);
            if (elect_one()) tma_load_2d(dst, &mp.wd, bar, cx, cy);
            if ((cy += 64) == f0 + 576) {
              cy = f0;
              cx += 64;
            }
            if (n > -5 && elect_one()) tma_load_2d(dst + (p < 5 ? 8192 : HALF), &mp.wd, bar, cx, cy);
            if (elect_one()) mbar_expect_tx(bar, n > -5 ? 16384 : 8192);
            if ((cy += 64) == f0 + 576) {
              cy = f0;
              cx += 64;
            }
            if (IMG && n == 8 && L + 1 < NLAYERS) poll_ge(&gs_.flag[FL_W + j], lds_u32(sb + S_EP) * 18u);
            if (++p == (n > 1 ? 7 : 5)) p = 0;
            if (p == 2) ph ^= 1;
          }
        }
      }
      }
    } else if (warp == 9) {
      cluster_wait();
      start();
      if (rb >= 16) {
        publish(false);
        named_bar_sync(6, 96);
#pragma unroll 1
        for (int n = 0; n < 2 * NLAYERS; ++n) {
          const int lane = min(tid_now() & 31, 17), w = lane >= 9, r = (rb - 16) * 8 + rank * 4 + (n & 1) * 2 + w;
          const unsigned int* fl = &gs_.flag[(n >> 1) * 1024 + r * 32 + 16 + lane - 9 * w];
          uint32_t todo = 0x3FFFFu;
#pragma unroll 1
          for (int it = 0; todo && it < SPIN_MAX; ++it) {
            unsigned int v;
            asm volatile("ld.relaxed.gpu.global.u32 %0, [%1];" : "=r"(v) : "l"(fl) : "memory");
            const uint32_t ready =
                __ballot_sync(0xffffffffu, (int)(v - ep1 * 8u) >= 0 && mbar_test(sb + B_ST + 8 * lane, ~n & 1)) & todo;
            todo &= ~ready;
            if ((ready >> (tid_now() & 31)) & 1) {
              mbar_expect_tx(sb + B_FX + 8 * lane, TILE);
              tma_load_3d(sb + lane * TILE, &mp.r, sb + B_FX + 8 * lane, (lane - 9 * w) * 64, r * 64 + 32, 0);
            }
            __syncwarp();
            if (H_SLEEP && todo == 0x3FFFFu) __nanosleep(H_SLEEP);
          }
        }
        if (elect_one()) gs_.epoch[blockIdx.x] = ep1;
      } else {
      auto fetch = [&](const CUtensorMap* map, uint32_t mask) {
        const int lane = tid_now() & 31;
        if ((mask >> lane) & 1)
          tma_load_3d_mc(sb + rank * HALF + lane * TILE, map, sb + B_FX + 72 * rank + 8 * lane, lane * 64, rb * 64 + rank * 32, 0);
        __syncwarp();
      };
      if ((tid_now() & 31) < 18) mbar_expect_tx(sb + B_FX + 8 * (tid_now() & 31), TILE);
      fetch(&mp.x0, (1u << X_EARLY) - 1);
      publish(true);
      {
        const int lane = tid_now() & 31;
        if (lane < 18) {
          const float4 w = ldg_cg_f4(gs_.wsum + 72 * j + 4 * lane);
          sts_u4(sb + S_WS + lane * 16, __float_as_uint(w.x), __float_as_uint(w.y), __float_as_uint(w.z), __float_as_uint(w.w));
        }
      }
#pragma unroll 1
      for (int n = 0; n < 2 * NLAYERS - 1; ++n) {
        if (n < NLAYERS) {
#pragma unroll 1
          for (int c = tid_now() & 31; c < 54; c += 32) {
            const int part = c / 18, i = c - 18 * part;
            const float* src = gs_.csq + part * 576 + 72 * j + 4 * (rank ? (i + 2) % 18 : i);
            float4 a = ldg_cg_f4(src), b = ldg_cg_f4(src + NQKV), d = ldg_cg_f4(src + 2 * NQKV);
            a.x += b.x; a.y += b.y; a.z += b.z; a.w += b.w;
            b = ldg_cg_f4(src + 3 * NQKV);
            a.x += b.x + d.x; a.y += b.y + d.y; a.z += b.z + d.z; a.w += b.w + d.w;
            const uint32_t h0 = pack_bf16(a.x, a.y), h1 = pack_bf16(a.z, a.w);
            const uint32_t ad = (i < 16 ? part * 256 + (((i >> 1) ^ (2 * part)) << 4) : 768 + ((part ^ 6) << 4)) + (i & 1) * 8;
            sts_f2(sb + OVF + ad, __uint_as_float(h0), __uint_as_float(h1));
            sts_f2(sb + OVF + (ad ^ 144), __uint_as_float(pack_bf16(a.x - bf_lo(h0), a.y - bf_hi(h0))),
                   __uint_as_float(pack_bf16(a.z - bf_lo(h1), a.w - bf_hi(h1))));
          }
          const int lane = tid_now() & 31;
          if (lane < 10) sts_u4(sb + OVF + 768 + (lane & 1) * 128 + (((3 + (lane >> 1)) ^ 6 ^ (lane & 1)) << 4), 0u, 0u, 0u, 0u);
          fence_proxy_async();
          warp_arrive(sb + B_AUX);
        }
        {
          const int lane = tid_now() & 31;
          const uint32_t bar = sb + B_FX + 8 * min(lane, 17);
#pragma unroll 1
          for (int it = 0; it < SPIN_MAX; ++it)
            if (__all_sync(0xffffffffu, mbar_test(bar, n & 1))) break;
          if (lane < 18) mbar_expect_tx(bar, TILE);
        }
        const unsigned int* fl = &gs_.flag[n * 512 + rb * 32 + rank * 16 + (tid_now() & 15)];
        if (LAZY) mbar_wait(sb + B_ST + 72 * rank, n & 1);
        uint32_t todo = 0x1FFu;
#pragma unroll 1
        for (int it = 0; todo && it < SPIN_MAX; ++it) {
          unsigned int v;
          asm volatile("ld.relaxed.gpu.global.u32 %0, [%1];" : "=r"(v) : "l"(fl) : "memory");
          const uint32_t ready = __ballot_sync(0xffffffffu, (int)(v - ep1 * 8u) >= 0) & todo;
          if (LAZY > 1 && (n & 1) && !ready && (todo & 0x7F)) __nanosleep(300);
          if (ready) {
            todo &= ~ready;
            fetch(&mp.r, ready);
          }
        }
      }
      uint32_t bid;
      asm volatile("mov.u32 %0, %%ctaid.x;" : "=r"(bid));
      if (elect_one()) gs_.epoch[bid] = ep1;
      }
    } else {
      cluster_wait();
      start();
      if (rb >= 16) {
      if (DN_PF && warp == 11) {
        mbar_wait(sb + B_ST + 64, 0);
#pragma unroll 1
        for (int u = 0; u < 18 * DN_PF; ++u) {
          if (elect_one()) tma_prefetch_2d(&mp.wd, 128 * (u / 18), ((rb - 16) * 2 + rank) * 1152 + 64 * (u % 18));
          __nanosleep(DN_NS);
        }
      }
      if (warp == 10) {
        const int t = (rb - 16) * 2 + rank;
        __nanosleep(H_DELAY);
#pragma unroll 1
        for (int kb = 0; kb < 11; ++kb) {
          if (kb < 9) {
            load_halves(sb + kb * SLOT, sb + B_NB + 8 * (kb & 3), 544 + 1152 * t, 1120 + 1152 * t, 64 * kb);
            if (elect_one()) mbar_expect_tx(sb + B_NB + 8 * (kb & 3), SLOT);
          }
          if (kb >= 2) {
            mbar_wait(sb + B_NB + 8 * ((kb - 2) & 3), ((kb - 2) >> 2) & 1);
            if (elect_one()) bulk_store(gs_.himg + (t * 9 + kb - 2) * 1024, sb + (kb - 2) * SLOT, SLOT);
          }
        }
        bulk_commit();
        bulk_wait<0>();
        if (elect_one()) signal_release(&gs_.flag[FL_W + 8]);
        poll_ge(&gs_.flag[FL_W + 8], ep1 * 4u);
        asm volatile("bar.arrive 6, 96;" ::: "memory");
      }
      } else {
      const int h = warp & 1;
      if (h) {
        const int lane = tid_now() & 31;
#pragma unroll 1
        for (int i = 0; i < 12; ++i) st_tagged(gs_.halo + (rb * 8 + j) * 384 + i * 32 + lane, 0u, 0u, 0u, 2 * ep1 - 1);
        if (lane < 16) st_tagged(gs_.stat + rb * 128 + (lane >> 3) * 64 + 8 * j + (lane & 7), 0u, 0u, 0u, 4 * ep1 - 1);
      }

      auto copy = [&](int hh, int c) {
        if (elect_one()) tma_store_3d(&mp.r, sb + hh * HALF + c * TILE, 64 * c, rb * 64 + hh * 32, 0);
        bulk_commit();
        bulk_wait<0>();
        __syncwarp();
        if (c < 3) asm volatile("fence.acq_rel.gpu;" ::: "memory");
      };
      float s1 = 0.f, s2 = 0.f;
      int kb = 0;
      uint32_t hn = 0;
      auto tile_stats = [&]() {
        const int lane = tid_now() & 31;
        const uint32_t ad = sb + h * HALF + kb * TILE + j * 1024 + (lane & 28) * 32 + (lane & 7) * 16;
        const uint4 u = lds_u4(ad), v = lds_u4(ad ^ 64);
        const uint32_t w[8] = {u.x, u.y, u.z, u.w, v.x, v.y, v.z, v.w};
        float a = 0.f, b = 0.f;
#pragma unroll
        for (int e = 0; e < 8; ++e) {
          const float lo = bf_lo(w[e]), hi = bf_hi(w[e]);
          s1 += lo;
          a += hi;
          s2 = fmaf(lo, lo, s2);
          b = fmaf(hi, hi, b);
        }
        s1 += a;
        s2 += b;
        ++kb;
      };
      unsigned int* fl = &gs_.flag[rb * 32];
#pragma unroll 1
      for (int n = 0; n < 2 * NLAYERS; ++n, fl += 512) {
        const int L = n >> 1;
        (void)L;
        {
          const int lane = tid_now() & 31;
#pragma unroll 1
          while (kb < 8 + (n & 1)) {
            mbar_wait(sb + B_FX + 72 * h + 8 * kb, n & 1);
            tile_stats();
            if (n == 0 && kb == j + 1) copy(h, j);
          }
          s1 = quad_sum(s1) * ((n & 1) ? 1.0f / DM : 1.0f / 512);
          s2 = fmaf(s1 * s1, (n & 1) ? -576.f : -512.f, quad_sum(s2));
          if (n & 1) {
            s2 = inv_sd(s2 * (1.0f / DM));
            s2 *= s2;
          }
          uint4* gs = gs_.stat + rb * 128 + h * 64;
          const uint32_t tag = 4 * ep1 + n;
          if ((lane & 3) == 0) st_tagged(gs + 8 * j + (lane >> 2), __float_as_uint(s1) & ~128u, __float_as_uint(s2) & ~128u, 0u, tag);
          s1 = s2 = 0.f;
          kb = 0;
          TA(14 + (n & 1) * 2);
          uint4 u, v;
#pragma unroll 1
          for (int it = 0; it < SPIN_MAX; ++it) {
            u = ld_tagged(gs + 2 * lane);
            v = ld_tagged(gs + 2 * lane + 1);
            if (__all_sync(0xffffffffu, u.w == tag && v.w == tag)) break;
          }
          if (n == 0) named_bar_sync(6, 96);
          if (n & 1) {
            sts_u32(sb + TAB + h * 512 + lane * 16 + 4, u.y);
            sts_u32(sb + TAB + h * 512 + lane * 16 + 12, v.y);
          } else {
            sts_u4(sb + TAB + h * 512 + lane * 16, u.x, u.y, v.x, v.y);
            fence_proxy_async();
          }
          warp_arrive(sb + B_SR);
          TA(15 + (n & 1) * 2);
        }
        if (!((n & 1) | h)) {
          const int lane = tid_now() & 31;
          const uint32_t dst = sb + (2 - rank) * TILE;
          mbar_wait(sb + B_QK, L);
          TA(18);
          if (rb) {
            auto attempt = [&](uint32_t b) {
              if (elect_one()) {
                mbar_expect_tx(sb + B_HP + 8 * b, 6144);
                bulk_load(dst, gs_.halo + (rb * 8 - 8 + j) * 384, 6144, sb + B_HP + 8 * b);
              }
            };
            attempt(hn & 1);
            __nanosleep(100);
#pragma unroll 1
            for (int it = 0; it < SPIN_MAX; ++it) {
              attempt(~hn & 1);
              mbar_wait(sb + B_HP + 8 * (hn & 1), (hn >> 1) & 1);
              ++hn;
              uint32_t bad = 0;
#pragma unroll
              for (int i = 0; i < 12; ++i) bad |= lds_u32(dst + lane * 16 + 12 + i * 512) ^ (2 * ep1 + L);
              if (__all_sync(0xffffffffu, bad == 0)) break;
            }
          } else {
#pragma unroll 1
            for (int i = 0; i < 12; ++i) sts_u4(dst + lane * 16 + i * 512, 0u, 0u, 0u, 0u);
            __syncwarp();
          }
          if (lane < 2) mbar_arrive(sb + B_NB + 16 * lane);
          TA(19);
          if (rb) {
            mbar_wait(sb + B_HP + 8 * (hn & 1), (hn >> 1) & 1);
            ++hn;
          }
        }
        if (n == 0 && h && (j & 5) == 0) {
          mbar_wait(sb + B_FX + 36 * j + 64, 0);
          copy(j >> 1, 8);
        }
        auto send = [&](int hh, int c) {
          TA(20 + (n & 1) * 20 + c);
          fence_proxy_async();
          if (elect_one()) tma_reduce_3d(&mp.r, sb + hh * HALF + c * TILE, 64 * c, rb * 64 + hh * 32, 0);
          bulk_commit();
        };
        if (!(n & 1)) {
          uint32_t tnext, t;
#pragma unroll 1
          for (int i = 0; i < 5; ++i) {
            const int c = i ? 2 * i - 1 + rank : 0;
            if (i == 1) {
              TA(20 + c);
              named_bar_sync(7 + h, 64);
              if (elect_one()) signal_release(fl + 16 * h + c, 2);
              TA(30 + c);
              continue;
            }
            mbar_wait(sb + B_ST + 72 * h + 8 * i, 0);
            while (true) {
              asm volatile("mov.u32 %0, %%clock;" : "=r"(t));
              if (i == 0 || (int)(t - tnext) >= 0) break;
              __nanosleep(40);
            }
            tnext = i ? tnext + PACE : t + PACE0 + rank * PACE_R;
            if (i == (n ? 4 : 2)) mbar_wait(sb + B_FX + 72 * h, 1);
            if (i == 4) mbar_wait(sb + B_FX + 72 - 72 * h, 1);
            send(h, c);
            bulk_wait<0>();
            if (elect_one()) signal_release(fl + 16 * h + c, i ? 2 : 1);
            TA(30 + c);
          }
        } else {
          if (IMG && n == 1 && NLAYERS > 1 && !h) {
#pragma unroll 1
            for (int s = rb; s < 18; s += 16) {
              const uint32_t bar = sb + B_HP + 8 * (hn & 1), dst = sb + (s >> 4) * HALF + 5 * TILE;
              mbar_wait(sb + B_ST + 72 * (s >> 4), 1);
              load_wq(dst, bar, s);
              mbar_wait(bar, (hn >> 1) & 1);
              ++hn;
              fence_proxy_async();
              __syncwarp();
              if (elect_one()) bulk_store(gs_.wimg + (j * 18 + s) * 1024, dst, SLOT);
            }
          }
#pragma unroll 1
          for (int a = h ^ 1; a < 9; a += 2) {
            mbar_wait(sb + B_ST + 72 + 8 * a, 1);
            send(1, a);
            mbar_wait(sb + B_ST + 8 * a, 1);
            send(0, a);
            if (n < 2 * NLAYERS - 1) {
              bulk_wait<0>();
              if (elect_one()) {
                signal_release(fl + 16 + a);
                signal_relaxed(fl + a);
                if (IMG && a == 1) {
                  signal_relaxed(&gs_.flag[FL_W + j], rb < 2 ? 2 : 1);
                  mbar_arrive(sb + B_S1);
                }
              }
              TA(50 + a);
#pragma unroll 1
              while (kb < min(a - 1, ST_END)) {
                mbar_wait(sb + B_FX + 72 * h + 8 * kb, 0);
                tile_stats();
              }
            }
          }
          bulk_wait<0>();
        }
      }
      }
    }
  } else {
    {
      const int t = threadIdx.x, lane = t & 31;
      uint4 sq[5], so[3];
      if (t < 16 * X_PF) asm volatile("prefetch.global.L2 [%0];" ::"l"(x0 + (size_t)(blockIdx.x * 16 + (t & 15)) * DM + (t >> 4) * 64));
#pragma unroll
      for (int i = 0; i < 5; ++i)
        sq[i] = ldg_u4(wqkv + (size_t)((blockIdx.x & 3) + (t >> 3) * 4 + 128 * i) * NQKV + (blockIdx.x >> 2) * 64 + (t & 7) * 8,
                       blockIdx.x < 108 && (i < 4 || t < 128));
#pragma unroll
      for (int i = 0; i < 3; ++i)
        so[i] = ldg_u4(wo + (size_t)((blockIdx.x - 32) * 6 + warp) * DM + (i * 32 + lane) * 8,
                       blockIdx.x - 32 < 96 && warp < 6 && (i < 2 || lane < 8));
      asm volatile("setmaxnreg.inc.sync.aligned.u32 240;");
      float c[8];
#pragma unroll
      for (int e = 0; e < 8; ++e) c[e] = 0.f;
#pragma unroll
      for (int i = 0; i < 5; ++i) {
        c[0] += bf_lo(sq[i].x); c[1] += bf_hi(sq[i].x); c[2] += bf_lo(sq[i].y); c[3] += bf_hi(sq[i].y);
        c[4] += bf_lo(sq[i].z); c[5] += bf_hi(sq[i].z); c[6] += bf_lo(sq[i].w); c[7] += bf_hi(sq[i].w);
      }
#pragma unroll
      for (int n = 4; n >= 2; n >>= 1) {
        const bool up = lane & (4 * n);
#pragma unroll
        for (int e = 0; e < n; ++e) c[e] = (up ? c[e + n] : c[e]) + __shfl_xor_sync(0xffffffffu, up ? c[e] : c[e + n], 4 * n);
      }
      sts_f2(sb + OVF + warp * 256 + (lane & 7) * 32 + (lane & 24), c[0], c[1]);
      float r = sum8(so[0]) + sum8(so[1]) + sum8(so[2]);
#pragma unroll
      for (int o = 1; o < 32; o <<= 1) r += __shfl_xor_sync(0xffffffffu, r, o);
      if (lane == 0 && blockIdx.x - 32 < 96 && warp < 6) gs_.wsum[(blockIdx.x - 32) * 6 + warp] = r;
      cluster_wait();
      warp_arrive(sb + B_J);
      TA0(13);
    }
    mbar_wait(sb + B_ROLE, 0);
    const bool helper = __shfl_sync(0xffffffffu, lds_u32(sb + S_ROLE), 0) >= 64;
    if (helper) {
      const int wg = warp >> 2;
      const uint32_t da0 = desc_lo_a(sb + wg * HALF), db0 = desc_lo_b(sb + RING, 4096);
      int p = 2;
      uint32_t ph = 0;
      auto mma = [&](float(&d)[64], int kb, bool add) {
        wgmma_fence();
#pragma unroll
        for (int k = 0; k < 4; ++k) wgmma_ss<128>(d, desc_from_lo(da0 + kb * 512 + k * 2), desc_64(db0 + p * 1024 + k * 64), add || k);
        wgmma_commit();
      };
      auto next = [&](bool rel, bool wait, bool more) {
        const int done = p == 0 ? 4 : p - 1;
        if (++p == 5) p = 0;
        if (p == 2) ph ^= 1;
        if (more) mbar_wait(sb + B_FULL + 8 * p, ph);
        if (wait) wgmma_wait<1>();
        release_slot(sb, done, rel);
      };
#pragma unroll 1
      for (uint32_t L = 0; L < NLAYERS; ++L) {
        uint32_t tag;
        uint4* dst;
        auto publish = [&](const uint32_t(&hh)[16], int t, int i) {
          const int b = (i / 3) * 8 + (i % 3) * 3;
          st_tagged(dst + ((t >> 2) * 16 + (t & 3) * 2) * 384 + i * 128, hh[b], hh[b + 1], i % 3 < 2 ? hh[b + 2] : 0u, tag);
        };
        uint32_t h0[16], h1[16], h2[16];
        float prod[32];
        {
          float acc0[64], acc1[64], acc2[64];
#pragma unroll
          for (int i = 0; i < 64; ++i) acc0[i] = acc1[i] = acc2[i] = 0.f;
          mbar_wait(sb + B_FULL + 8 * p, ph);
#pragma unroll 1
          for (int kb = 0; kb < 9; ++kb) {
            mbar_wait(sb + B_FX + 72 * wg + 8 * kb, 0);
            if (kb == 0) TS(9);
            mma(acc0, kb, true);
            next(kb > 0, true, true);
            mma(acc1, kb, true);
            next(true, true, true);
            mma(acc2, kb, true);
            next(true, true, true);
          }
#pragma unroll
          for (int i = 0; i < 16; ++i) {
            h0[i] = pack_bf16(acc0[2 * i] * acc0[32 + 2 * i], acc0[2 * i + 1] * acc0[33 + 2 * i]);
            h1[i] = pack_bf16(acc1[2 * i] * acc1[32 + 2 * i], acc1[2 * i + 1] * acc1[33 + 2 * i]);
          }
          tag = 2 * lds_u32(sb + S_EP) + L;
          dst = gs_.hx + (lds_u32(sb + S_ROLE) * 2 - 128 + rank * 4 + wg) * 8 * 384 + (tid_now() & 127);
          wgmma_wait<0>();
#pragma unroll
          for (int i = 0; i < 32; ++i) prod[i] = acc2[i] * acc2[32 + i];
        }
        TS(10);
        float acc[64];
#pragma unroll 1
        for (int t = 3; t < 8; ++t) {
          mma(acc, 0, false);
#pragma unroll
          for (int i = 0; i < 32; ++i) asm volatile("" : "+f"(prod[i]));
#pragma unroll
          for (int i = 0; i < 16; ++i) h2[i] = pack_bf16(prod[2 * i], prod[2 * i + 1]);
          if (t == 4) {
            stage_done(sb, 8, 1);
            mbar_wait(sb + B_FX + 72 * wg + 8, 1);
          }
          next(true, false, true);
#pragma unroll
          for (int kb = 1; kb < 9; ++kb) {
            mma(acc, kb, true);
            if (kb < 7) {
              publish(h2, t - 1, kb - 1);
              if (t < 5) publish(h0, t - 3, kb - 1);
            }
            if (t == (kb < 8 ? 4 : 3)) mbar_wait(sb + B_FX + 72 * wg + 8 * ((kb + 1) % 9), 1);
            next(true, true, kb < 8 || t < 7);
            if ((t & 3) == 3) stage_done(sb, kb - 1, 1);
          }
#pragma unroll
          for (int i = 0; i < 16; ++i) h0[i] = h1[i];
          wgmma_wait<0>();
#pragma unroll
          for (int i = 0; i < 32; ++i) prod[i] = acc[i] * acc[32 + i];
        }
        TS(11);
#pragma unroll
        for (int i = 0; i < 16; ++i) h2[i] = pack_bf16(prod[2 * i], prod[2 * i + 1]);
#pragma unroll
        for (int i = 0; i < 6; ++i) publish(h2, 7, i);
        release_slot(sb, p == 0 ? 4 : p - 1);
        stage_done(sb, 8, 1);
        TS(12);
      }
    } else
#pragma unroll 1
    for (uint32_t L = 0; L < NLAYERS; ++L) {
      {
        const int wg = warp >> 2;
        float acc[108];
        const uint32_t da0 = desc_lo_a(sb + wg * HALF), db0 = desc_lo_b(sb + RING, 4096);
        int p = 2;
        uint32_t ph = L;
        auto step = [&](int kb, auto U, auto FIRST) {
          constexpr int u = decltype(U)::value, first = decltype(FIRST)::value == 1;
          constexpr bool last = decltype(FIRST)::value == 2;
          wgmma_fence();
#pragma unroll
          for (int k = 0; k < 2; ++k)
            wgmma_ss<216>(acc, desc_from_lo(da0 + kb * 512 + u * 4 + k * 2), desc_from_lo(db0 + p * 1024 + k * 128), !first || u || k);
          wgmma_commit();
          if (last && wg) asm volatile("bar.arrive 5, 256;" ::: "memory");
          const int prev = p == 0 ? 4 : p - 1;
          if (++p == 5) p = 0;
          if (p == 2) ph ^= 1;
          if (!last) {
            if (u) mbar_wait2(sb + B_FX + 72 * wg + 8 * kb + 8, 0, sb + B_FULL + 8 * p, ph);
            else mbar_wait(sb + B_FULL + 8 * p, ph);
          }
          if (!first || u) {
            wgmma_wait<1>();
            release_slot(sb, prev);
          }
        };
        mbar_wait2(sb + B_FX + 72 * wg, 0, sb + B_FULL + 8 * p, ph);
        TR(1);
        step(0, IC<0>{}, IC<1>{});
        step(0, IC<1>{}, IC<1>{});
        float s1[2] = {0.f, 0.f}, s2[2] = {0.f, 0.f};
        bool todo = true;
        const int stop = wg ? 8 : Q_H;
        auto last_tile = [&]() {
          const int lane = tid_now() & 31;
#pragma unroll
          for (int r = 0; r < 2; ++r) {
            const uint32_t ad = sb + wg * HALF + 8 * TILE + (warp & 3) * 2048 + r * 1024 + (lane & 28) * 32 + (lane & 7) * 16;
            const uint4 u = lds_u4(ad), v = lds_u4(ad ^ 64);
            const uint32_t w[8] = {u.x, u.y, u.z, u.w, v.x, v.y, v.z, v.w};
            float a = 0.f, b = 0.f, c = 0.f, d = 0.f;
#pragma unroll
            for (int e = 0; e < 8; ++e) {
              const float lo = bf_lo(w[e]), hi = bf_hi(w[e]);
              a += lo;
              b += hi;
              c = fmaf(lo, lo, c);
              d = fmaf(hi, hi, d);
            }
            s1[r] = quad_sum(a + b) * (1.0f / 64);
            s2[r] = fmaf(s1[r] * s1[r], -64.f, quad_sum(c + d));
          }
          todo = false;
        };
#pragma unroll 1
        for (int kb = 1; kb < 9; ++kb) {
          TR(1 + kb);
          if (Q_H < 8 && kb == stop) mbar_wait(sb + B_FX + 72 * wg + 64, 0);
          if (todo && kb >= (wg ? Q_ST1 : Q_ST0) && __all_sync(0xffffffffu, mbar_test(sb + B_FX + 72 * wg + 64, 0))) last_tile();
          if (kb == stop) break;
          step(kb, IC<0>{}, IC<0>{});
          step(kb, IC<1>{}, IC<0>{});
        }
        const int tid = tid_now(), lane = tid & 31, g = lane >> 2, q = lane & 3;
        if (lane == 0 && wg == 0) mbar_arrive(sb + B_QK);
        mbar_wait2(sb + B_SR, 0, sb + B_AUX, L);
        float2 st0 = lds_f2(sb + TAB + (warp * 16 + g) * 8), st1 = lds_f2(sb + TAB + (warp * 16 + g) * 8 + 64);
        s1[0] -= st0.x;
        s1[1] -= st1.x;
        st0.x = fmaf(s1[0], 1.0f / 9, st0.x);
        st1.x = fmaf(s1[1], 1.0f / 9, st1.x);
        st0.y = fmaf(s1[0] * s1[0], 512.f / 9, st0.y + s2[0]);
        st1.y = fmaf(s1[1] * s1[1], 512.f / 9, st1.y + s2[1]);
        if (wg == 0) named_bar_sync(5, 256);
        wgmma_fence();
        wgmma_rs<216>(acc, q ? 0u : pack_bf16(-st0.x, -st0.x), q ? 0u : pack_bf16(-st1.x, -st1.x), 0u, 0u, desc_sbo(desc_lo_b(sb + OVF, 256), 0), 1);
        wgmma_commit();
        if (Q_H < 8) {
#pragma unroll 1
          for (int kb = stop; kb < 8; ++kb) {
            step(kb, IC<0>{}, IC<0>{});
            step(kb, IC<1>{}, IC<0>{});
          }
        }
        step(8, IC<0>{}, IC<0>{});
        step(8, IC<1>{}, IC<2>{});
        TR(10);
        st0.y = inv_sd(st0.y * (1.0f / DM));
        st1.y = inv_sd(st1.y * (1.0f / DM));
        const uint32_t ep1 = lds_u32(sb + S_EP), role = lds_u32(sb + S_ROLE);
        const bool first = (warp & 5) == 0 && role < 4;
        const bool e0 = 2 * q > g, e1 = 2 * q + 1 > g;
        float fs[2][2], fp[2][2], fb[2];
        {
          const float k0 = __shfl_sync(0xffffffffu, st0.y, 8 * q), k1 = __shfl_sync(0xffffffffu, st0.y, 8 * q + 4);
          const float c = 0.23570226039551584f * 1.4426950408889634f;
          fp[0][0] = e0 ? 1.f : k0;
          fp[0][1] = e1 ? 1.f : k1;
          fp[1][0] = e0 ? k0 : 1.f;
          fp[1][1] = e1 ? k1 : 1.f;
#pragma unroll
          for (int i = 0; i < 4; ++i) fs[i >> 1][i & 1] = fp[i >> 1][i & 1] * ((i >> 1) ? st1.y : st0.y) * c;
          fb[0] = first && e0 ? -INFINITY : 0.f;
          fb[1] = first && e1 ? -INFINITY : 0.f;
        }
        const int sw = (warp & 1) ? warp + 3 : warp + 1;
        const uint64_t nbp = sw >= 8 ? (uint64_t)(gs_.halo + (role * 2 + rank) * 384 + (warp & 2) * 96 + lane)
                                     : (uint64_t)(smem + (sw >> 2) * HALF + (2 + 2 * (sw & 1) - rank) * TILE + (sw & 2) * 1536 + lane * 16);
        const uint32_t nbb = lane ? mapa(sb + B_RX + 8 * wg, rank ^ 1) : mapa(sb + B_NB + 8 * (sw & 7), rank);
        const bool nba = lane ? lane == 1 : sw < 8;
        if (tid == 128 * wg) mbar_expect_tx(sb + B_OX + 8 * wg, 10240);
        __syncwarp();
        wgmma_wait<0>();
        release_slot(sb, 4);
        TS(1);
        uint32_t Q[2][9], K[3][9], V[3][9];
        auto pack = [&](auto R) {
          constexpr int r = decltype(R)::value;
#pragma unroll
          for (int i = 0; i < 9; ++i) {
            const int c = (i + 9 - r) % 9, jv = c < 8 ? 64 + 4 * c : 104;
            V[2][i] = movm(pack_bf16(acc[jv + 2] * st1.y, acc[jv + 3] * st1.y));
          }
#pragma unroll
          for (int i = 0; i < 9; ++i) {
            const int c = (i + 9 - r) % 9, jk = c < 8 ? 32 + 4 * c : 100;
            K[2][i] = pack_bf16(acc[jk + 2] * st1.y, acc[jk + 3] * st1.y);
          }
#pragma unroll
          for (int i = 0; i < 6; ++i) {
            const uint32_t(&d)[9] = i < 3 ? K[2] : V[2];
            st_tagged_any(nbp + i * 512, d[3 * (i % 3)], d[3 * (i % 3) + 1], d[3 * (i % 3) + 2], 2 * ep1 + L);
          }
          __syncwarp();
          mbar_arrive_if(nbb, nba);
#pragma unroll
          for (int i = 0; i < 9; ++i) {
            const int c = (i + 9 - r) % 9, jq = c < 8 ? 4 * c : 96, jk = c < 8 ? 32 + 4 * c : 100, jv = c < 8 ? 64 + 4 * c : 104;
            V[1][i] = movm(pack_bf16(acc[jv], acc[jv + 1]));
            Q[0][i] = pack_bf16(acc[jq], acc[jq + 1]);
            Q[1][i] = pack_bf16(acc[jq + 2], acc[jq + 3]);
            K[1][i] = pack_bf16(acc[jk], acc[jk + 1]);
          }
        };
        if (rank) pack(IC<1>{});
        else pack(IC<0>{});
        uint32_t qf[4][2], ql[4][2];
        float sc[4][3][4];
        auto logits = [&](int t) {
#pragma unroll
          for (int h = 0; h < 4; ++h) {
            mma_1688(sc[h][t], ql[h][0], ql[h][1], K[t][2 * h + 2]);
            mma_16816(sc[h][t], qf[h][0], qf[h][1], Q[0][2 * h + 1], Q[1][2 * h + 1], K[t][2 * h], K[t][2 * h + 1]);
          }
        };
#pragma unroll
        for (int i = 0; i < 8; ++i) {
          qf[i >> 1][i & 1] = q >= (i >> 1) ? Q[i & 1][i & 6] : 0u;
          ql[i >> 1][i & 1] = q <= (i >> 1) ? Q[i & 1][(i & 6) + 2] : 0u;
        }
        logits(1);
        logits(2);
        float2 ws[9];
#pragma unroll
        for (int i = 0; i < 9; ++i) ws[i] = lds_f2(sb + S_WS + i * 32 + 8 * q);
        uint32_t of[9][2];
        float o0[9][2];
        auto rows = [&](auto R, float(&o)[9][2]) {
          constexpr int r = decltype(R)::value;
          float pr[4][2], mx[4];
#pragma unroll
          for (int h = 0; h < 4; ++h) {
            pr[h][0] = fmaf(e0 ? sc[h][r][2 * r] : sc[h][r + 1][2 * r], fs[r][0], r ? 0.f : fb[0]);
            pr[h][1] = fmaf(e1 ? sc[h][r][2 * r + 1] : sc[h][r + 1][2 * r + 1], fs[r][1], r ? 0.f : fb[1]);
            mx[h] = fmaxf(pr[h][0], pr[h][1]);
          }
#pragma unroll
          for (int i = 0; i < 8; ++i) mx[i & 3] = fmaxf(mx[i & 3], __shfl_xor_sync(0xffffffffu, mx[i & 3], 1 + (i >> 2)));
#pragma unroll
          for (int h = 0; h < 4; ++h) {
#pragma unroll
            for (int e = 0; e < 2; ++e) asm("ex2.approx.ftz.f32 %0, %1;" : "=f"(pr[h][e]) : "f"(pr[h][e] - mx[h]));
            mx[h] = pr[h][0] + pr[h][1];
            pr[h][0] *= fp[r][0];
            pr[h][1] *= fp[r][1];
          }
#pragma unroll
          for (int i = 0; i < 8; ++i) mx[i & 3] += __shfl_xor_sync(0xffffffffu, mx[i & 3], 1 + (i >> 2));
          const uint32_t me = (e0 ? 0xFFFFu : 0u) | (e1 ? 0xFFFF0000u : 0u);
          uint32_t pp[4];
#pragma unroll
          for (int h = 0; h < 4; ++h) {
            pp[h] = pack_bf16(pr[h][0], pr[h][1]);
            asm("rcp.approx.ftz.f32 %0, %1;" : "=f"(mx[h]) : "f"(mx[h]));
          }
#pragma unroll
          for (int i = 0; i < 9; ++i) {
            const int h = i < 4 ? 0 : i < 5 ? 1 : 2;
            float d[4];
            mma_16816_z(d, pp[h] & me, pp[h + 1] & me, pp[h] & ~me, pp[h + 1] & ~me, V[r][i], V[r + 1][i]);
            const bool up = i == 2 * h + 2 ? q > h : i > 2 * h + 2;
            const float inv = up ? mx[h + 1] : mx[h];
            o[i][0] = (up ? d[2] : d[0]) * inv;
            o[i][1] = (up ? d[3] : d[1]) * inv;
            of[i][r] = pack_bf16(o[i][0], o[i][1]);
          }
        };
        auto shift = [&](const float(&o)[9][2]) {
          float a = 0.f, b = 0.f, c = 0.f;
#pragma unroll
          for (int i = 0; i < 3; ++i) {
            a = fmaf(o[i][0], ws[i].x, fmaf(o[i][1], ws[i].y, a));
            b = fmaf(o[i + 3][0], ws[i + 3].x, fmaf(o[i + 3][1], ws[i + 3].y, b));
            c = fmaf(o[i + 6][0], ws[i + 6].x, fmaf(o[i + 6][1], ws[i + 6].y, c));
          }
          return a + b + c;
        };
        rows(IC<1>{}, o0);
        float sh1 = shift(o0);
        mbar_wait3(sb + B_FULL, L ^ 1, sb + B_RX + 8 * wg, L, sb + B_NB + 8 * warp, L);
#pragma unroll
        for (int i = 0; i < 6; ++i) {
          const uint4 u = lds_u4(sb + wg * HALF + (2 + 2 * (warp & 1) - rank) * TILE + (warp & 2) * 1536 + lane * 16 + i * 512);
          uint32_t(&d)[9] = i < 3 ? K[0] : V[0];
          d[3 * (i % 3)] = u.x;
          d[3 * (i % 3) + 1] = u.y;
          d[3 * (i % 3) + 2] = u.z;
        }
        TS(3);
        logits(0);
        rows(IC<0>{}, o0);
        TS(5);
        float wa[3][32];
        const uint32_t dw0 = desc_lo_b(sb + RING, 0);
        wgmma_fence();
#pragma unroll
        for (int k = 0; k < 5; ++k)
          wgmma_rs<64>(wa[0], of[2 * k][0], of[2 * k][1], k < 4 ? of[2 * k + 1][0] : 0u, k < 4 ? of[2 * k + 1][1] : 0u,
                       desc_sbo(dw0 + k * 128, k < 4 ? 1024 : 0), k);
        wgmma_commit();
        const uint32_t xa = sb + wg * HALF + 3 * TILE + (warp & 3) * 2048 + lane * 16;
        const uint32_t xr = mapa(xa + (rank ^ 1) * TILE, rank ^ 1), xb = mapa(sb + B_OX + 8 * wg, rank ^ 1);
#pragma unroll
        for (int i = 0; i < 4; ++i) st_async_u4(xr + i * 512, xb, of[2 * i][0], of[2 * i][1], of[2 * i + 1][0], of[2 * i + 1][1]);
        float sh0 = fmaf(quad_sum(shift(o0)), 1.0f / DM, st0.x * 0.125f);
        sh1 = fmaf(quad_sum(sh1), 1.0f / DM, st1.x * 0.125f);
        st_async_u4(xr + 2 * TILE, xb, of[8][0], of[8][1], __float_as_uint(sh0), __float_as_uint(sh1));
        wgmma_wait<0>();
        stage_tile(wa[0], 1.f, -sh0, 1.f, -sh1, sb, 0, 0, 1);
        TS(6);
        uint4 xv[5];
        auto issue = [&](auto I, auto PART) {
          constexpr int i = decltype(I)::value, part = decltype(PART)::value;
          const uint32_t lo = dw0 + (2 * i - 1) * (WOA / 16);
          if (part & 1) mbar_wait(sb + B_FULL + 8 * i, (i == 1) ^ L);
          wgmma_fence();
          if (part & 1) {
#pragma unroll
            for (int k = 0; k < 4; ++k)
              wgmma_rs<64>(wa[i % 3], of[2 * k][0], of[2 * k][1], of[2 * k + 1][0], of[2 * k + 1][1], desc_sbo(lo + k * 128, 1024), k);
          }
          if (part & 2) {
            wgmma_rs<64>(wa[i % 3], of[8][0], of[8][1], xv[4].x, xv[4].y, desc_sbo(lo + 512, WOA), 1);
#pragma unroll
            for (int k = 0; k < 4; ++k)
              wgmma_rs<64>(wa[i % 3], xv[k].x, xv[k].y, xv[k].z, xv[k].w, desc_sbo(lo + WOA / 16 + k * 128, 1024), 1);
          }
          wgmma_commit();
        };
        issue(IC<1>{}, IC<1>{});
        if (q < 2) sts_u32(sb + TAB + (warp * 16 + g + 8 * q) * 8, __float_as_uint(q ? sh1 : sh0));
        mbar_wait(sb + B_OX + 8 * wg, L);
#pragma unroll
        for (int i = 0; i < 5; ++i) xv[i] = lds_u4(xa + rank * TILE + (i < 4 ? i * 512 : 2 * TILE));
        sh0 += __uint_as_float(xv[4].z);
        sh1 += __uint_as_float(xv[4].w);
        TS(4);
        issue(IC<1>{}, IC<2>{});
        wgmma_wait<0>();
        release_slot(sb, 0);
        stage_tile(wa[1], 1.f, -sh0, 1.f, -sh1, sb, 1 + rank, 1, 1);
        mbar_wait(sb + B_ST, 0);
        issue(IC<2>{}, IC<3>{});
        issue(IC<3>{}, IC<3>{});
        wgmma_wait<1>();
        release_slot(sb, 1);
        issue(IC<4>{}, IC<3>{});
        stage_tile(wa[2], 1.f, -sh0, 1.f, -sh1, sb, 3 + rank, 0, 0);
        wgmma_wait<1>();
        release_slot(sb, 2);
        stage_tile(wa[0], 1.f, -sh0, 1.f, -sh1, sb, 5 + rank, 0, 0);
        wgmma_wait<0>();
        release_slot(sb, 3);
        release_slot(sb, 4);
        stage_tile(wa[1], 1.f, -sh0, 1.f, -sh1, sb, 7 + rank, 2, 7);
        TS(7);
      }
      uint32_t hreg[9][16];
      {
        const int wg = warp >> 2;
        float acc[64];
        int p = 0;
        uint32_t ph = L;
        const uint32_t da0 = desc_lo_a(sb + wg * HALF), db0 = desc_lo_b(sb + RING, 8192);
        float prod[32];
        {
          float acc0[64], acc1[64], acc2[64];
#pragma unroll
          for (int i = 0; i < 64; ++i) acc0[i] = acc1[i] = acc2[i] = 0.f;
          auto step = [&](float(&d)[64], int kb, bool rel) {
            mbar_wait(sb + B_FULL + 8 * p, ph);
            wgmma_fence();
#pragma unroll
            for (int k = 0; k < 4; ++k)
              wgmma_ss<128>(d, desc_from_lo(da0 + kb * 512 + k * 2), desc_from_lo(db0 + p * 1024 + k * 128), 1);
            wgmma_commit();
            wgmma_wait<1>();
            release_slot(sb, p == 0 ? 4 : p - 1, rel);
            if (++p == 5) p = 0;
            if (p == 2) ph ^= 1;
          };
#pragma unroll 1
          for (int kb = 0; kb < 9; ++kb) {
            mbar_wait(sb + B_FX + 72 * wg + 8 * kb, 1);
            if (kb == 0) TS(9);
            TR(16 + kb);
            step(acc0, kb, kb > 0);
            step(acc1, kb, true);
            step(acc2, kb, true);
          }
#pragma unroll
          for (int i = 0; i < 16; ++i) {
            hreg[0][i] = pack_bf16(acc0[2 * i] * acc0[32 + 2 * i], acc0[2 * i + 1] * acc0[33 + 2 * i]);
            hreg[1][i] = pack_bf16(acc1[2 * i] * acc1[32 + 2 * i], acc1[2 * i + 1] * acc1[33 + 2 * i]);
          }
          mbar_wait(sb + B_FULL + 8 * p, ph);
          wgmma_wait<0>();
#pragma unroll
          for (int i = 0; i < 32; ++i) prod[i] = acc2[i] * acc2[32 + i];
        }
#pragma unroll
        for (int t = 2; t < 7; ++t)
#pragma unroll
          for (int i = 0; i < 16; ++i) hreg[t][i] = 0u;
        TS(10);
#pragma unroll 1
        for (int t = 3; t < 8; ++t) {
          wgmma_fence();
#pragma unroll
          for (int k = 0; k < 4; ++k)
            wgmma_ss<128>(acc, desc_from_lo(da0 + k * 2), desc_from_lo(db0 + p * 1024 + k * 128), k != 0);
          wgmma_commit();
          release_slot(sb, p == 0 ? 4 : p - 1);
#pragma unroll
          for (int i = 0; i < 32; ++i) asm volatile("" : "+f"(prod[i]));
#pragma unroll
          for (int i = 0; i < 16; ++i) hreg[8][i] = pack_bf16(prod[2 * i], prod[2 * i + 1]);
          if (++p == 5) p = 0;
          if (p == 2) ph ^= 1;
          mbar_wait(sb + B_FULL + 8 * p, ph);
#pragma unroll 1
          for (int kb = 1; kb < 9; ++kb) {
            wgmma_fence();
#pragma unroll
            for (int k = 0; k < 4; ++k)
              wgmma_ss<128>(acc, desc_from_lo(da0 + kb * 512 + k * 2), desc_from_lo(db0 + p * 1024 + k * 128), 1);
            wgmma_commit();
            if (kb == 1) {
#pragma unroll
              for (int tt = 2; tt < 7; ++tt)
                if (t == tt + 1) {
#pragma unroll
                  for (int i = 0; i < 16; ++i) asm volatile("mov.b32 %0, %1;" : "=r"(hreg[tt][i]) : "r"(hreg[8][i]));
                }
            }
            const int done = p == 0 ? 4 : p - 1;
            if (++p == 5) p = 0;
            if (p == 2) ph ^= 1;
            if (GU_PRE) mbar_wait(sb + B_FULL + 8 * p, ph);
            wgmma_wait<1>();
            release_slot(sb, done);
            if (!GU_PRE) mbar_wait(sb + B_FULL + 8 * p, ph);
          }
          wgmma_wait<0>();
#pragma unroll
          for (int i = 0; i < 32; ++i) prod[i] = acc[i] * acc[32 + i];
          TR(32 + t);
        }
        auto tail = [&](auto NN) {
          constexpr int N = decltype(NN)::value;
          float acc[N / 2];
          const uint32_t db = desc_lo_b(sb + RING, N == 64 ? 8192 : 4096);
          auto mma = [&](int kb, bool first) {
            wgmma_fence();
#pragma unroll
            for (int k = 0; k < 4; ++k)
              wgmma_ss<N>(acc, desc_from_lo(da0 + kb * 512 + k * 2), desc_64(db + p * 1024 + k * 64), !first || k);
            wgmma_commit();
          };
          mma(0, true);
          release_slot(sb, p == 0 ? 4 : p - 1);
#pragma unroll
          for (int i = 0; i < 32; ++i) asm volatile("" : "+f"(prod[i]));
#pragma unroll
          for (int i = 0; i < 16; ++i) hreg[7][i] = pack_bf16(prod[2 * i], prod[2 * i + 1]);
          if (++p == 5) p = 0;
          if (p == 2) ph ^= 1;
          mbar_wait(sb + B_FULL + 8 * p, ph);
          uint4 hx[3] = {};
          const uint4* src = gs_.hx;
          uint32_t tag = 0;
          if (N == 64) {
            src += (lds_u32(sb + S_ROLE) * 2 + rank) * 384 + (tid_now() & 127);
            tag = 2 * lds_u32(sb + S_EP) + L;
          }
          auto fetch = [&]() {
#pragma unroll
            for (int i = 0; i < 3; ++i) hx[i] = ld_tagged(src + i * 128);
          };
#pragma unroll 1
          for (int kb = 1; kb < 9; ++kb) {
            if (N == 128 && kb == T_HOLD) named_bar_sync(5, 256);
            mma(kb, false);
            if (N == 64 && kb == T_LEAD) asm volatile("bar.arrive 5, 256;" ::: "memory");
            if (N == 64 && kb == KH) fetch();
            const int done = p == 0 ? 4 : p - 1;
            if (++p == 5) p = 0;
            if (p == 2) ph ^= 1;
            mbar_wait(sb + B_FULL + 8 * p, ph);
            wgmma_wait<1>();
            release_slot(sb, done);
          }
          if (N == 64) {
#pragma unroll 1
            for (int it = 0; it < SPIN_MAX; ++it) {
              if (__all_sync(0xffffffffu, hx[0].w == tag && hx[1].w == tag && (hx[2].w | hx[2].z) == tag)) break;
              fetch();
            }
            const uint32_t w[8] = {hx[0].x, hx[0].y, hx[0].z, hx[1].x, hx[1].y, hx[1].z, hx[2].x, hx[2].y};
#pragma unroll
            for (int i = 0; i < 8; ++i) hreg[8][8 + i] = w[i] ^ hx[i / 3].w ^ tag;
#pragma unroll
            for (int i = 8; i < 16; ++i) asm volatile("" : "+r"(hreg[8][i]));
          }
          wgmma_wait<0>();
#pragma unroll
          for (int i = 0; i < N / 8; ++i) hreg[8][i] = pack_bf16(acc[2 * i] * acc[N / 4 + 2 * i], acc[2 * i + 1] * acc[N / 4 + 2 * i + 1]);
        };
        if (wg) tail(IC<64>{});
        else tail(IC<128>{});
      }
      TS(11);
      {
        float accA[32], accB[32];
#pragma unroll
        for (int i = 16; i < 32; ++i) accB[i] = 0.f;
        int p = 1;
        uint32_t ph = L;
        const uint32_t db0 = desc_lo_b(sb + RING, 8192);
        int prev = 0, left = 35;
        auto stage = [&](auto S, auto NU, bool rel) {
          constexpr int s = decltype(S)::value;
          const uint32_t dlo = p < 5 ? db0 + p * 1024 : db0 - RING / 16 + 1024 + p * 512, dv = p < 5 ? 512 : HALF / 16;
          wgmma_fence();
#pragma unroll
          for (int v = 0; v < decltype(NU)::value; ++v) {
            const int u = 2 * s + v, kq = u % 9;
#pragma unroll
            for (int k = 0; k < 4; ++k)
              wgmma_rs<64>(u >= 9 ? accB : accA, hreg[kq][4 * k], hreg[kq][4 * k + 1], hreg[kq][4 * k + 2], hreg[kq][4 * k + 3],
                           desc_from_lo(dlo + v * dv + k * 128), (kq | k) != 0);
          }
          wgmma_commit();
          const int done = prev;
          prev = p;
          --left;
          if (++p == (left > 0 ? 7 : 5)) p = 0;
          if (p == 2) ph ^= 1;
          if (decltype(NU)::value == 2) mbar_wait(sb + B_FULL + 8 * p, ph ^ (p >= 5));
          if (rel) {
            wgmma_wait<1>();
            release_slot(sb, done, done < 5 || left > 1);
          }
        };
        stage(IC<0>{}, IC<2>{}, false);
        release_slot(sb, 0);
        mbar_wait(sb + B_SR, 1);
        release_slot(sb, 5);
        release_slot(sb, 6);
        const uint32_t ta = sb + TAB + warp * 128 + (tid_now() & 28) * 2;
        const float2 t0 = lds_f2(ta), t1 = lds_f2(ta + 64);
        const float m0 = t0.y, c0 = t0.x, m1 = t1.y, c1 = t1.x;
#pragma unroll 1
        for (int i = 0; i < 4; ++i) {
          stage(IC<1>{}, IC<2>{}, true);
          if (i) stage_tile<2, 4>(accB, m0, c0, m1, c1, sb, 2 * i - 1, 0, 0);
          stage(IC<2>{}, IC<2>{}, true);
          if (i) stage_done(sb, 2 * i - 1, 1);
          stage(IC<3>{}, IC<2>{}, true);
          stage(IC<4>{}, IC<2>{}, true);
          stage(IC<5>{}, IC<2>{}, true);
          stage_tile<0, 2>(accA, m0, c0, m1, c1, sb, 2 * i, 0, 0);
          TR(48 + 2 * i);
          stage(IC<6>{}, IC<2>{}, true);
          stage_tile<2, 4>(accA, m0, c0, m1, c1, sb, 2 * i, 0, 0);
          stage(IC<7>{}, IC<2>{}, true);
          stage_done(sb, 2 * i, 1);
          if (i == 3 && (tid_now() & 31) == 0) mbar_arrive(sb + B_XF);
          stage(IC<8>{}, IC<2>{}, true);
          stage(IC<0>{}, IC<2>{}, true);
          if (IMG && i == 2 && L + 1 < NLAYERS) mbar_wait(sb + B_S1, 0);
          if (i == 3) mbar_wait(sb + B_XF, L);
          stage_tile<0, 2>(accB, m0, c0, m1, c1, sb, 2 * i + 1, 0, 0);
          TR(49 + 2 * i);
        }
        stage(IC<1>{}, IC<2>{}, true);
        stage_tile<2, 4>(accB, m0, c0, m1, c1, sb, 7, 7, DN_LATE ? 0 : 1);
        stage(IC<2>{}, IC<2>{}, true);
        if (DN_LATE) stage_done(sb, 7, 1);
        stage(IC<3>{}, IC<2>{}, true);
        stage(IC<4>{}, IC<1>{}, true);
        wgmma_wait<0>();
        release_slot(sb, 1);
        stage_tile(accA, m0, c0, m1, c1, sb, 8, 8, 1);
        TR(56);
        TS(12);
      }
    }
  }
}

__global__ void probe_kernel() {}

typedef CUresult (*PFN_tmEncode)(CUtensorMap*, CUtensorMapDataType, cuuint32_t, void*, const cuuint64_t*,
                                 const cuuint64_t*, const cuuint32_t*, const cuuint32_t*, CUtensorMapInterleave,
                                 CUtensorMapSwizzle, CUtensorMapL2promotion, CUtensorMapFloatOOBfill);

static void encode_2d(PFN_tmEncode fn, CUtensorMap* m, const void* ptr, uint64_t inner, uint64_t outer, uint32_t box_inner,
                      uint32_t box_outer) {
  cuuint64_t dims[2] = {inner, outer};
  cuuint64_t strides[1] = {inner * 2};
  cuuint32_t box[2] = {box_inner, box_outer};
  cuuint32_t estr[2] = {1, 1};
  fn(m, CU_TENSOR_MAP_DATA_TYPE_BFLOAT16, 2, const_cast<void*>(ptr), dims, strides, box, estr,
     CU_TENSOR_MAP_INTERLEAVE_NONE, box_inner < 64 ? CU_TENSOR_MAP_SWIZZLE_64B : CU_TENSOR_MAP_SWIZZLE_128B,
     box_inner < 64 ? CU_TENSOR_MAP_L2_PROMOTION_L2_128B : CU_TENSOR_MAP_L2_PROMOTION_L2_256B, CU_TENSOR_MAP_FLOAT_OOB_FILL_NONE);
}

static void encode_3d(PFN_tmEncode fn, CUtensorMap* m, const void* ptr, uint64_t d0, uint64_t d1, uint64_t d2, uint64_t s1,
                      uint64_t s2, uint32_t b0, uint32_t b1, uint32_t b2, CUtensorMapL2promotion prom) {
  cuuint64_t dims[3] = {d0, d1, d2};
  cuuint64_t strides[2] = {s1, s2};
  cuuint32_t box[3] = {b0, b1, b2};
  cuuint32_t estr[3] = {1, 1, 1};
  fn(m, CU_TENSOR_MAP_DATA_TYPE_BFLOAT16, 3, const_cast<void*>(ptr), dims, strides, box, estr, CU_TENSOR_MAP_INTERLEAVE_NONE,
     b0 < 64 ? CU_TENSOR_MAP_SWIZZLE_64B : CU_TENSOR_MAP_SWIZZLE_128B, prom, CU_TENSOR_MAP_FLOAT_OOB_FILL_NONE);
}

}

extern "C" void kernel_launch(void* const* d_in, const int* in_sizes, int n_in, void* d_out, int out_size) {
  const __nv_bfloat16* x0 = (const __nv_bfloat16*)d_in[0];
  const __nv_bfloat16* wqkv = (const __nv_bfloat16*)d_in[1];
  const __nv_bfloat16* wo = (const __nv_bfloat16*)d_in[2];
  const __nv_bfloat16* wg = (const __nv_bfloat16*)d_in[4];
  const __nv_bfloat16* wu = (const __nv_bfloat16*)d_in[5];
  const __nv_bfloat16* wd = (const __nv_bfloat16*)d_in[6];
  static PFN_tmEncode enc = nullptr;
  if (!enc) {
    void* fn = nullptr;
    cudaDriverEntryPointQueryResult qr;
    cudaGetDriverEntryPoint("cuTensorMapEncodeTiled", &fn, cudaEnableDefault, &qr);
    enc = (PFN_tmEncode)fn;
  }
  Maps mp;
  encode_3d(enc, &mp.x0, x0, DM, SEQ / 2, 2, DM * 4, DM * 2, 64, 32, 2, CU_TENSOR_MAP_L2_PROMOTION_L2_256B);
  encode_3d(enc, &mp.r, d_out, DM, SEQ / 2, 2, DM * 4, DM * 2, 64, 32, 2, CU_TENSOR_MAP_L2_PROMOTION_L2_256B);
  encode_3d(enc, &mp.wq, wqkv, 576, 576, 3, NQKV * 2, 576 * 2, 64, 32, 3, CU_TENSOR_MAP_L2_PROMOTION_L2_128B);
  encode_2d(enc, &mp.wo, wo, DM, DM, 64, 72);
  encode_2d(enc, &mp.wg, wg, FF, DM, 64, 64);
  encode_2d(enc, &mp.wu, wu, FF, DM, 64, 64);
  encode_2d(enc, &mp.wd, wd, DM, FF, 64, 64);
  encode_3d(enc, &mp.tg, wg, 32, DM, FF / 32, FF * 2, 64, 32, 64, 2, CU_TENSOR_MAP_L2_PROMOTION_L2_128B);
  encode_3d(enc, &mp.tu, wu, 32, DM, FF / 32, FF * 2, 64, 32, 64, 2, CU_TENSOR_MAP_L2_PROMOTION_L2_128B);
  encode_2d(enc, &mp.hg, wg, FF, DM, 32, 64);
  encode_2d(enc, &mp.hu, wu, FF, DM, 32, 64);
  cudaFuncSetAttribute(mega_kernel, cudaFuncAttributeMaxDynamicSharedMemorySize, SMEM_BYTES);
  static int small_gpc = -1;
  if (small_gpc < 0) {
    cudaFuncSetAttribute(probe_kernel, cudaFuncAttributeMaxDynamicSharedMemorySize, SMEM_BYTES);
    cudaFuncSetAttribute(probe_kernel, cudaFuncAttributeNonPortableClusterSizeAllowed, 1);
    int n[2] = {0, 0};
    for (int i = 0; i < 2; ++i) {
      cudaLaunchConfig_t cfg = {};
      cfg.gridDim = dim3(128);
      cfg.blockDim = dim3(384);
      cfg.dynamicSmemBytes = SMEM_BYTES;
      cudaLaunchAttribute at;
      at.id = cudaLaunchAttributeClusterDimension;
      at.val.clusterDim.x = 8 << i;
      at.val.clusterDim.y = at.val.clusterDim.z = 1;
      cfg.attrs = &at;
      cfg.numAttrs = 1;
      if (cudaOccupancyMaxActiveClusters(&n[i], probe_kernel, &cfg) != cudaSuccess) cudaGetLastError();
    }
    small_gpc = n[0] == 15 && n[1] == 7;
  }
  mega_kernel<<<NCTA, 384, SMEM_BYTES, cudaStreamPerThread>>>(mp, x0, wqkv, wo, (__nv_bfloat16*)d_out, small_gpc);
}
```
